```python
import torch

def _softmax(x, axis=-1):
    return torch.softmax(x, dim=axis)
def _gelu(x):
    return torch.nn.functional.gelu(x, approximate="tanh")
def _silu(x):
    return torch.nn.functional.silu(x)
def _sigmoid(x):
    return torch.sigmoid(x)
def _layernorm(x, axis=-1, eps=1e-5):
    m = x.mean(dim=axis, keepdim=True)
    v = x.var(dim=axis, keepdim=True, unbiased=False)
    return (x - m) / torch.sqrt(v + eps)
def _scatter_add(tgt, idx, src, axis=0):
    return tgt.clone().index_add_(axis, idx, src)
def _segment_sum(src, seg, n):
    out = torch.zeros((n,) + src.shape[1:], dtype=src.dtype)
    return out.index_add_(0, seg, src)
def _pad(x, pw):
    flat = tuple(v for pair in reversed(pw) for v in pair)
    return torch.nn.functional.pad(x, flat)

kernel_name = 'concat_heads__linear_kernel_hedgehog__ssm_conv_s4__prompt'

def setup_inputs():

    _w = (lambda a: (lambda t: t.to(torch.bfloat16) if t.is_floating_point() else t)(torch.as_tensor(a)))
    def _A_setup():
        B, S, D, H = 1, 2048, 640, 32
        Dh = D // H
        return {
            "x": _w((lambda *s: torch.randn(*s, dtype=torch.bfloat16) * 0.4)(B, S, D)),
            "wqkv": _w((lambda *s: torch.randn(*s, dtype=torch.bfloat16) * 0.4)(D, 3 * D)),
            "w_phi": _w((lambda *s: torch.randn(*s, dtype=torch.bfloat16) * 0.4)(H, Dh, Dh) * (Dh ** -0.5)),
            "wo": _w((lambda *s: torch.randn(*s, dtype=torch.bfloat16) * 0.05)(D, D)),
        }
    _A_in = _A_setup()

    def _B_setup():
        B, L, D, N = 1, 2048, 640, 128
        A_re = -(lambda _x: torch.exp(torch.as_tensor(_x)))((lambda *s: torch.randn(*s, dtype=torch.bfloat16) * 3.2)(D, N))
        A_im = torch.pi * (lambda *s: torch.randn(*s, dtype=torch.bfloat16) * 0.2)(D, N)
        B_re = (lambda *s: torch.randn(*s, dtype=torch.bfloat16) * 0.4)(D, N)
        B_im = (lambda *s: torch.randn(*s, dtype=torch.bfloat16) * 0.4)(D, N)
        C_re = (lambda *s: torch.randn(*s, dtype=torch.bfloat16) * 0.4)(D, N)
        C_im = (lambda *s: torch.randn(*s, dtype=torch.bfloat16) * 0.4)(D, N)
        log_dt = (lambda *s: torch.randn(*s, dtype=torch.bfloat16) * 0.2)(D) * 0.5 - 4.0
        Dskip = (lambda *s: torch.randn(*s, dtype=torch.bfloat16) * 0.4)(D)
        return {
            "u": _w((lambda *s: torch.randn(*s, dtype=torch.bfloat16) * 0.05)(B, L, D)),
            "A_re": _w(A_re),
            "A_im": _w(A_im),
            "B_re": _w(B_re),
            "B_im": _w(B_im),
            "C_re": _w(C_re),
            "C_im": _w(C_im),
            "log_dt": _w(log_dt),
            "Dskip": _w(Dskip),
        }
    _B_in = _B_setup()

    return {
        "A_x": _A_in["x"],
        "A_wqkv": _A_in["wqkv"],
        "A_w_phi": _A_in["w_phi"],
        "A_wo": _A_in["wo"],
        "B_u": _B_in["u"],
        "B_A_re": _B_in["A_re"],
        "B_A_im": _B_in["A_im"],
        "B_B_re": _B_in["B_re"],
        "B_B_im": _B_in["B_im"],
        "B_C_re": _B_in["C_re"],
        "B_C_im": _B_in["C_im"],
        "B_log_dt": _B_in["log_dt"],
        "B_Dskip": _B_in["Dskip"],
    }

def reference(A_x, A_wqkv, A_w_phi, A_wo, B_u, B_A_re, B_A_im, B_B_re, B_B_im, B_C_re, B_C_im, B_log_dt, B_Dskip):
    def _A_ref(x, wqkv, w_phi, wo):
        B, S, D = x.shape
        H = 32; Dh = D // H
        qkv = (lambda x, *d: x.permute(*d))((x @ wqkv).reshape(B, S, 3, H, Dh), 2, 0, 3, 1, 4)
        q, k, v = qkv[0], qkv[1], qkv[2]
        pq = torch.einsum("bhsd,hdf->bhsf", q, w_phi)
        pk = torch.einsum("bhsd,hdf->bhsf", k, w_phi)
        phi_q = torch.concatenate([_softmax(pq, axis=-1), _softmax(-pq, axis=-1)], axis=-1)
        phi_k = torch.concatenate([_softmax(pk, axis=-1), _softmax(-pk, axis=-1)], axis=-1)
        kv = torch.einsum("bhsf,bhsd->bhfd", phi_k, v)
        z  = torch.einsum("bhsf->bhf", phi_k)
        num = torch.einsum("bhqf,bhfd->bhqd", phi_q, kv)
        den = torch.einsum("bhqf,bhf->bhq", phi_q, z)[..., None] + 1e-6
        o = num / den
        return (lambda x, *d: x.permute(*d))(o, 0, 2, 1, 3).reshape(B, S, D) @ wo

    def _B_ref(u, A_re, A_im, B_re, B_im, C_re, C_im, log_dt, Dskip):
        Bsz, L, D = u.shape
        dt = torch.exp(log_dt)[:, None]
        A = A_re + 1j * A_im
        Bc = B_re + 1j * B_im
        Cc = C_re + 1j * C_im
        logdA = dt * A
        dB = dt * Bc
        l = (lambda x, dt: x.to(dt))(torch.arange(L), A_re.dtype)
        P = torch.exp(logdA[:, :, None] * l[None, None, :])
        K = torch.einsum("dn,dnl,dn->dl", Cc, P, dB).real
        L2 = 2 * L
        Kp = _pad(K, ((0, 0), (0, L)))
        up = (lambda x, *d: x.permute(*d))(u, 0, 2, 1)
        up = _pad(up, ((0, 0), (0, 0), (0, L)))
        Kf = (lambda x, axes=(-2,-1): torch.fft.rfft2(x.float(), dim=axes))(Kp[:, None, :], axes=(-2, -1))
        Uf = (lambda x, axes=(-2,-1): torch.fft.rfft2(x.float(), dim=axes))(up[:, :, None, :], axes=(-2, -1))
        Yf = Uf * Kf[None, :, :, :]
        y = (lambda x, s, axes=(-2,-1): torch.fft.irfft2(x, s=s, dim=axes).to(torch.bfloat16))(Yf, (1, L2), axes=(-2, -1))[:, :, 0, :L]
        y = (lambda x, *d: x.permute(*d))(y, 0, 2, 1) + u * Dskip[None, None, :]
        return y

    a = _A_ref(A_x, A_wqkv, A_w_phi, A_wo)
    b = _B_ref(B_u, B_A_re, B_A_im, B_B_re, B_B_im, B_C_re, B_C_im, B_log_dt, B_Dskip)
    return torch.concatenate([a, b], axis=-1)
```

```cpp
#include <cuda_runtime.h>
#include <cuda.h>
#include <cuda_bf16.h>
#include <cuda_fp16.h>
#include <stdint.h>

#define ROT 256

#define WO_FIRST BAR_MAIN

namespace {

constexpr int NCTA = 128;
constexpr int SPIN_LIMIT = 1 << 22;

constexpr uint32_t STAGE    = 47104;
constexpr uint32_t OFF_W128 = 16384;
constexpr uint32_t OFF_W16  = 40960;
constexpr uint32_t SM_PHIK  = 0;
constexpr uint32_t PHIK_S   = 2080;
constexpr uint32_t SM_V     = 41600;
constexpr uint32_t SM_KVST  = SM_V;
constexpr uint32_t SM_KVB   = 0;
constexpr uint32_t SM_OST   = 28800;
constexpr uint32_t SM_WO    = 81920;
constexpr uint32_t SM_WPHI  = 2 * STAGE + 28672;
constexpr uint32_t SM_B     = 4 * STAGE;
constexpr uint32_t SM_KZ    = SM_B;
constexpr uint32_t SM_KG    = SM_B + 6528;
constexpr uint32_t SM_KG2   = 2 * STAGE;
constexpr uint32_t SM_PT0   = 66176;
constexpr uint32_t SM_H     = SM_PT0 + 4864;
constexpr uint32_t SM_W     = SM_H + 4352;
constexpr uint32_t SM_XCH2  = SM_W + 4096;
constexpr uint32_t SM_O4    = SM_B + 7168;
constexpr uint32_t SM_PT1   = SM_B + 23552;
constexpr uint32_t SM_UB1   = SM_B + 28416;
constexpr uint32_t SM_XCH   = SM_B + 33152;
constexpr uint32_t SM_UB0   = SM_B + 38656;
constexpr uint32_t UB_C = 2368, UB_Z = 20;
constexpr uint32_t SM_WP    = SM_B + 35200;
constexpr uint32_t SM_MISC  = SM_B + 43456;
constexpr uint32_t BAR_FULL   = SM_MISC;
constexpr uint32_t BAR_EMPTY  = SM_MISC + 32;
constexpr uint32_t BAR_WO     = SM_MISC + 64;
constexpr uint32_t BAR_OFULL  = SM_MISC + 72;
constexpr uint32_t BAR_OEMPTY = SM_MISC + 112;
constexpr uint32_t BAR_UB     = SM_MISC + 152;
constexpr uint32_t BAR_EPOCH  = SM_MISC + 168;
constexpr uint32_t BAR_MAIN   = SM_MISC + 176;
constexpr uint32_t BAR_S6     = SM_MISC + 184;
constexpr uint32_t BAR_S7     = SM_MISC + 192;
constexpr uint32_t BAR_COUNT2 = 0xF0u | (0x1Fu << 14) | (7u << 22);
constexpr uint32_t SM_EPOCH = SM_MISC + 296;
constexpr uint32_t BAR_PHI    = SM_MISC + 224;
constexpr uint32_t BAR_KGD    = SM_MISC + 232;
constexpr uint32_t BAR_RDY    = SM_MISC + 240;
constexpr uint32_t BAR_XF     = SM_MISC + 256;
constexpr uint32_t BAR_PRM    = SM_MISC + 264;
constexpr uint32_t BAR_PRF    = SM_MISC + 216;
constexpr uint32_t BAR_K0     = SM_MISC + 208;
constexpr uint32_t BAR_FREE   = SM_MISC + 248;
constexpr uint32_t SM_CMAX  = SM_KZ + 4 * 1296;
constexpr uint32_t BAR_KVB    = SM_MISC + 272;
constexpr uint32_t BAR_WP     = SM_MISC + 200;
constexpr uint32_t SM_STAMP = SM_MISC + 320;
constexpr uint32_t SMEM_BYTES = SM_MISC + 576;

__device__ __align__(1024) __nv_bfloat16 g_uT[640 * 2048];
__device__ __align__(1024) uint32_t g_yT[640 * 1024];
__device__ __align__(1024) __nv_bfloat16 g_O[2048 * 640];
__device__ __align__(1024) float g_kv[2 * 8 * 3600];
__device__ __align__(1024) unsigned g_cnt[40 * 32];
constexpr int CNT_START = 0, CNT_KV = 1, CNT_O = 9, CNT_T1 = 25, CNT_Y = 29;

#define STAMP(i)
#define STAMP_FLUSH(lo, hi)
#define STAMP_IF(c, i)

struct Params {
  uint8_t tile_of_sm[192];
  unsigned nsm;
  uint8_t bar_count[36];
  CUtensorMap x, w128, w16, wo, o, ost, ut, out;
  const uint32_t* wphi;
  const __nv_bfloat16* u;
  const uint16_t* ssm[6];
  const uint16_t *logdt, *dskip;
  __nv_bfloat16* outp;
};

__device__ __forceinline__ void mbar_init(uint32_t b, int c) { asm volatile("mbarrier.init.shared::cta.b64 [%0], %1;" ::"r"(b), "r"(c) : "memory"); }
__device__ __forceinline__ void mbar_expect(uint32_t b, int bytes) { asm volatile("mbarrier.arrive.expect_tx.shared::cta.b64 _, [%0], %1;" ::"r"(b), "r"(bytes) : "memory"); }
__device__ __forceinline__ void mbar_arrive(uint32_t b) { asm volatile("mbarrier.arrive.shared::cta.b64 _, [%0];" ::"r"(b) : "memory"); }
__device__ __forceinline__ void mbar_wait(uint32_t b, int parity) {
  asm volatile("{\n.reg .pred p;\n.reg .u32 n;\nmov.u32 n, %2;\n"
               "WAIT:\nmbarrier.try_wait.parity.shared::cta.b64 p, [%0], %1;\n@p bra DONE;\n"
               "sub.u32 n, n, 1;\nsetp.ne.u32 p, n, 0;\n@p bra WAIT;\nDONE:\n}" ::"r"(b), "r"(parity), "n"(SPIN_LIMIT) : "memory");
}
__device__ __forceinline__ void tma2d(uint32_t dst, const CUtensorMap* m, uint32_t bar, int c0, int c1) {
  asm volatile("cp.async.bulk.tensor.2d.shared::cluster.global.mbarrier::complete_tx::bytes [%0], [%1, {%3,%4}], [%2];" ::"r"(dst), "l"(m), "r"(bar), "r"(c0), "r"(c1) : "memory");
}
__device__ __forceinline__ void tma3d(uint32_t dst, const CUtensorMap* m, uint32_t bar, int c0, int c1, int c2) {
  asm volatile("cp.async.bulk.tensor.3d.shared::cluster.global.mbarrier::complete_tx::bytes [%0], [%1, {%3,%4,%5}], [%2];" ::"r"(dst), "l"(m), "r"(bar), "r"(c0), "r"(c1), "r"(c2) : "memory");
}
__device__ __forceinline__ void tma4d(uint32_t dst, const CUtensorMap* m, uint32_t bar, int c0, int c1, int c2, int c3) {
  asm volatile("cp.async.bulk.tensor.4d.shared::cluster.global.mbarrier::complete_tx::bytes [%0], [%1, {%3,%4,%5,%6}], [%2];" ::"r"(dst), "l"(m), "r"(bar), "r"(c0), "r"(c1), "r"(c2), "r"(c3) : "memory");
}
__device__ __forceinline__ void tma2d_store(const CUtensorMap* m, uint32_t src, int c0, int c1) {
  asm volatile("cp.async.bulk.tensor.2d.global.shared::cta.bulk_group [%0, {%2,%3}], [%1];" ::"l"(m), "r"(src), "r"(c0), "r"(c1) : "memory");
}
__device__ __forceinline__ void fence_async_smem() { asm volatile("fence.proxy.async.shared::cta;" ::: "memory"); }
__device__ __forceinline__ void fence_async_global() { asm volatile("fence.proxy.async.global;" ::: "memory"); }
__device__ __forceinline__ void bulk_commit_wait() {
  asm volatile("cp.async.bulk.commit_group;" ::: "memory");
  asm volatile("cp.async.bulk.wait_group 0;" ::: "memory");
}
template <int ID, int N> __device__ __forceinline__ void bar_sync() { asm volatile("bar.sync %0, %1;" ::"n"(ID), "n"(N) : "memory"); }
template <int ID, int N> __device__ __forceinline__ void bar_arrive() { asm volatile("bar.arrive %0, %1;" ::"n"(ID), "n"(N) : "memory"); }
__device__ __forceinline__ void wg_fence() { asm volatile("wgmma.fence.sync.aligned;" ::: "memory"); }
__device__ __forceinline__ void wg_commit() { asm volatile("wgmma.commit_group.sync.aligned;" ::: "memory"); }
template <int N> __device__ __forceinline__ void wg_wait() { asm volatile("wgmma.wait_group.sync.aligned %0;" ::"n"(N) : "memory"); }
template <int N> __device__ __forceinline__ void pin(float* d) {
#pragma unroll
  for (int i = 0; i < N; i++) asm volatile("" : "+f"(d[i])::"memory");
}
template <int N> __device__ __forceinline__ void pin(uint32_t* d) {
#pragma unroll
  for (int i = 0; i < N; i++) asm volatile("" : "+r"(d[i])::"memory");
}
__device__ __forceinline__ uint32_t dlo(uint32_t addr, uint32_t lbo) { return ((addr & 0x3FFFF) >> 4) | ((lbo >> 4) << 16); }
__host__ __device__ constexpr uint32_t dhi(uint32_t sbo, uint32_t sw) { return (sbo >> 4) | (sw << 30); }
template <int V> struct IC { __host__ __device__ constexpr operator int() const { return V; } };
template <int I, int N, class F> __device__ __forceinline__ void static_for(F&& f) {
  if constexpr (I < N) { f(IC<I>{}); static_for<I + 1, N>(f); }
}
__device__ __forceinline__ uint32_t pack_bf16(float lo, float hi) {
  uint32_t r;
  asm("cvt.rn.bf16x2.f32 %0, %1, %2;" : "=r"(r) : "f"(hi), "f"(lo));
  return r;
}
__device__ __forceinline__ uint32_t pack_f16(float lo, float hi) {
  uint32_t r;
  asm("cvt.rn.f16x2.f32 %0, %1, %2;" : "=r"(r) : "f"(hi), "f"(lo));
  return r;
}
__device__ __forceinline__ float ex2(float x) { float r; asm("ex2.approx.ftz.f32 %0, %1;" : "=f"(r) : "f"(x)); return r; }
__device__ __forceinline__ float rcp(float x) { float r; asm("rcp.approx.ftz.f32 %0, %1;" : "=f"(r) : "f"(x)); return r; }
__device__ __forceinline__ float bf2f(uint32_t h) { return __uint_as_float(h << 16); }
__device__ __forceinline__ void sts32(uint32_t a, uint32_t v) { asm volatile("st.shared.u32 [%0], %1;" ::"r"(a), "r"(v) : "memory"); }
__device__ __forceinline__ void sts16(uint32_t a, uint32_t v) { asm volatile("st.shared.u16 [%0], %1;" ::"r"(a), "h"((uint16_t)v) : "memory"); }
__device__ __forceinline__ void sts64(uint32_t a, uint32_t x, uint32_t y) { asm volatile("st.shared.v2.u32 [%0], {%1,%2};" ::"r"(a), "r"(x), "r"(y) : "memory"); }
__device__ __forceinline__ void sts128(uint32_t a, uint32_t x, uint32_t y, uint32_t z, uint32_t w) { asm volatile("st.shared.v4.u32 [%0], {%1,%2,%3,%4};" ::"r"(a), "r"(x), "r"(y), "r"(z), "r"(w) : "memory"); }
__device__ __forceinline__ uint32_t lds32(uint32_t a) { uint32_t v; asm volatile("ld.shared.u32 %0, [%1];" : "=r"(v) : "r"(a) : "memory"); return v; }
__device__ __forceinline__ uint32_t lds16(uint32_t a) { uint16_t v; asm volatile("ld.shared.u16 %0, [%1];" : "=h"(v) : "r"(a) : "memory"); return v; }
__device__ __forceinline__ uint2 lds64(uint32_t a) { uint2 v; asm volatile("ld.shared.v2.u32 {%0,%1}, [%2];" : "=r"(v.x), "=r"(v.y) : "r"(a) : "memory"); return v; }
__device__ __forceinline__ uint4 lds128(uint32_t a) { uint4 v; asm volatile("ld.shared.v4.u32 {%0,%1,%2,%3}, [%4];" : "=r"(v.x), "=r"(v.y), "=r"(v.z), "=r"(v.w) : "r"(a) : "memory"); return v; }
__device__ __forceinline__ uint32_t movm(uint32_t a) { uint32_t d; asm volatile("movmatrix.sync.aligned.m8n8.trans.b16 %0, %1;" : "=r"(d) : "r"(a)); return d; }
__device__ __forceinline__ void signal(int c) {
  asm volatile("red.release.gpu.global.add.u32 [%0], 1;" ::"l"(&g_cnt[c * 32]) : "memory");
}
__device__ __forceinline__ void wait_count(int c, unsigned target) {
  asm volatile("{\n.reg .pred p;\n.reg .u32 n, v;\nmov.u32 n, %2;\n"
               "WAIT:\nld.relaxed.gpu.global.u32 v, [%0];\nsub.u32 v, v, %1;\nsetp.ge.s32 p, v, 0;\n@p bra DONE;\n"
               "sub.u32 n, n, 1;\nsetp.ne.u32 p, n, 0;\n@p bra WAIT;\nDONE:\nfence.acquire.gpu;\n}" ::"l"(&g_cnt[c * 32]), "r"(target), "n"(SPIN_LIMIT) : "memory");
}

template <int OA, uint32_t HA, int OB, uint32_t HB> __device__ __forceinline__ void mma_qkv192(float* d, uint32_t a, uint32_t b) {
  asm volatile("{\n.reg .pred p;\nsetp.ne.b32 p, 1, 0;\n.reg .b32 ta, tb;\n.reg .b64 da, db;\nadd.u32 ta, %96, %98;\nmov.b64 da, {ta, %99};\nadd.u32 tb, %97, %100;\nmov.b64 db, {tb, %101};\n"
    "wgmma.mma_async.sync.aligned.m64n192k16.f32.bf16.bf16 {%0,%1,%2,%3,%4,%5,%6,%7,%8,%9,%10,%11,%12,%13,%14,%15,%16,%17,%18,%19,%20,%21,%22,%23,%24,%25,%26,%27,%28,%29,%30,%31,%32,%33,%34,%35,%36,%37,%38,%39,%40,%41,%42,%43,%44,%45,%46,%47,%48,%49,%50,%51,%52,%53,%54,%55,%56,%57,%58,%59,%60,%61,%62,%63,%64,%65,%66,%67,%68,%69,%70,%71,%72,%73,%74,%75,%76,%77,%78,%79,%80,%81,%82,%83,%84,%85,%86,%87,%88,%89,%90,%91,%92,%93,%94,%95}, da, db, p,1,1,0,1;\n}\n"
    : "+f"(d[0]),"+f"(d[1]),"+f"(d[2]),"+f"(d[3]),"+f"(d[4]),"+f"(d[5]),"+f"(d[6]),"+f"(d[7]),"+f"(d[8]),"+f"(d[9]),"+f"(d[10]),"+f"(d[11]),"+f"(d[12]),"+f"(d[13]),"+f"(d[14]),"+f"(d[15]),"+f"(d[16]),"+f"(d[17]),"+f"(d[18]),"+f"(d[19]),"+f"(d[20]),"+f"(d[21]),"+f"(d[22]),"+f"(d[23]),"+f"(d[24]),"+f"(d[25]),"+f"(d[26]),"+f"(d[27]),"+f"(d[28]),"+f"(d[29]),"+f"(d[30]),"+f"(d[31]),"+f"(d[32]),"+f"(d[33]),"+f"(d[34]),"+f"(d[35]),"+f"(d[36]),"+f"(d[37]),"+f"(d[38]),"+f"(d[39]),"+f"(d[40]),"+f"(d[41]),"+f"(d[42]),"+f"(d[43]),"+f"(d[44]),"+f"(d[45]),"+f"(d[46]),"+f"(d[47]),"+f"(d[48]),"+f"(d[49]),"+f"(d[50]),"+f"(d[51]),"+f"(d[52]),"+f"(d[53]),"+f"(d[54]),"+f"(d[55]),"+f"(d[56]),"+f"(d[57]),"+f"(d[58]),"+f"(d[59]),"+f"(d[60]),"+f"(d[61]),"+f"(d[62]),"+f"(d[63]),"+f"(d[64]),"+f"(d[65]),"+f"(d[66]),"+f"(d[67]),"+f"(d[68]),"+f"(d[69]),"+f"(d[70]),"+f"(d[71]),"+f"(d[72]),"+f"(d[73]),"+f"(d[74]),"+f"(d[75]),"+f"(d[76]),"+f"(d[77]),"+f"(d[78]),"+f"(d[79]),"+f"(d[80]),"+f"(d[81]),"+f"(d[82]),"+f"(d[83]),"+f"(d[84]),"+f"(d[85]),"+f"(d[86]),"+f"(d[87]),"+f"(d[88]),"+f"(d[89]),"+f"(d[90]),"+f"(d[91]),"+f"(d[92]),"+f"(d[93]),"+f"(d[94]),"+f"(d[95])
    : "r"(a),"r"(b),"n"(OA),"n"(HA),"n"(OB),"n"(HB));
}
template <int OA, uint32_t HA, int OB, uint32_t HB> __device__ __forceinline__ void mma_qkv48(float* d, uint32_t a, uint32_t b) {
  asm volatile("{\n.reg .pred p;\nsetp.ne.b32 p, 1, 0;\n.reg .b32 ta, tb;\n.reg .b64 da, db;\nadd.u32 ta, %24, %26;\nmov.b64 da, {ta, %27};\nadd.u32 tb, %25, %28;\nmov.b64 db, {tb, %29};\n"
    "wgmma.mma_async.sync.aligned.m64n48k16.f32.bf16.bf16 {%0,%1,%2,%3,%4,%5,%6,%7,%8,%9,%10,%11,%12,%13,%14,%15,%16,%17,%18,%19,%20,%21,%22,%23}, da, db, p,1,1,0,1;\n}\n"
    : "+f"(d[0]),"+f"(d[1]),"+f"(d[2]),"+f"(d[3]),"+f"(d[4]),"+f"(d[5]),"+f"(d[6]),"+f"(d[7]),"+f"(d[8]),"+f"(d[9]),"+f"(d[10]),"+f"(d[11]),"+f"(d[12]),"+f"(d[13]),"+f"(d[14]),"+f"(d[15]),"+f"(d[16]),"+f"(d[17]),"+f"(d[18]),"+f"(d[19]),"+f"(d[20]),"+f"(d[21]),"+f"(d[22]),"+f"(d[23])
    : "r"(a),"r"(b),"n"(OA),"n"(HA),"n"(OB),"n"(HB));
}
template <int OB, uint32_t HB> __device__ __forceinline__ void mma_phi80(float* d, uint32_t a0, uint32_t a1, uint32_t a2, uint32_t a3, uint32_t b) {
  asm volatile("{\n.reg .pred p;\nsetp.ne.b32 p, 1, 0;\n.reg .b32 tb;\n.reg .b64 db;\nadd.u32 tb, %44, %45;\nmov.b64 db, {tb, %46};\n"
    "wgmma.mma_async.sync.aligned.m64n80k16.f32.bf16.bf16 {%0,%1,%2,%3,%4,%5,%6,%7,%8,%9,%10,%11,%12,%13,%14,%15,%16,%17,%18,%19,%20,%21,%22,%23,%24,%25,%26,%27,%28,%29,%30,%31,%32,%33,%34,%35,%36,%37,%38,%39}, {%40,%41,%42,%43}, db, p,1,1,1;\n}\n"
    : "+f"(d[0]),"+f"(d[1]),"+f"(d[2]),"+f"(d[3]),"+f"(d[4]),"+f"(d[5]),"+f"(d[6]),"+f"(d[7]),"+f"(d[8]),"+f"(d[9]),"+f"(d[10]),"+f"(d[11]),"+f"(d[12]),"+f"(d[13]),"+f"(d[14]),"+f"(d[15]),"+f"(d[16]),"+f"(d[17]),"+f"(d[18]),"+f"(d[19]),"+f"(d[20]),"+f"(d[21]),"+f"(d[22]),"+f"(d[23]),"+f"(d[24]),"+f"(d[25]),"+f"(d[26]),"+f"(d[27]),"+f"(d[28]),"+f"(d[29]),"+f"(d[30]),"+f"(d[31]),"+f"(d[32]),"+f"(d[33]),"+f"(d[34]),"+f"(d[35]),"+f"(d[36]),"+f"(d[37]),"+f"(d[38]),"+f"(d[39])
    : "r"(a0),"r"(a1),"r"(a2),"r"(a3),"r"(b),"n"(OB),"n"(HB));
}
template <int OB, uint32_t HB> __device__ __forceinline__ void mma_phi80_z(float* d, uint32_t a0, uint32_t a1, uint32_t a2, uint32_t a3, uint32_t b) {
  asm volatile("{\n.reg .pred p;\nsetp.ne.b32 p, 0, 0;\n.reg .b32 tb;\n.reg .b64 db;\nadd.u32 tb, %44, %45;\nmov.b64 db, {tb, %46};\n"
    "wgmma.mma_async.sync.aligned.m64n80k16.f32.bf16.bf16 {%0,%1,%2,%3,%4,%5,%6,%7,%8,%9,%10,%11,%12,%13,%14,%15,%16,%17,%18,%19,%20,%21,%22,%23,%24,%25,%26,%27,%28,%29,%30,%31,%32,%33,%34,%35,%36,%37,%38,%39}, {%40,%41,%42,%43}, db, p,1,1,1;\n}\n"
    : "=f"(d[0]),"=f"(d[1]),"=f"(d[2]),"=f"(d[3]),"=f"(d[4]),"=f"(d[5]),"=f"(d[6]),"=f"(d[7]),"=f"(d[8]),"=f"(d[9]),"=f"(d[10]),"=f"(d[11]),"=f"(d[12]),"=f"(d[13]),"=f"(d[14]),"=f"(d[15]),"=f"(d[16]),"=f"(d[17]),"=f"(d[18]),"=f"(d[19]),"=f"(d[20]),"=f"(d[21]),"=f"(d[22]),"=f"(d[23]),"=f"(d[24]),"=f"(d[25]),"=f"(d[26]),"=f"(d[27]),"=f"(d[28]),"=f"(d[29]),"=f"(d[30]),"=f"(d[31]),"=f"(d[32]),"=f"(d[33]),"=f"(d[34]),"=f"(d[35]),"=f"(d[36]),"=f"(d[37]),"=f"(d[38]),"=f"(d[39])
    : "r"(a0),"r"(a1),"r"(a2),"r"(a3),"r"(b),"n"(OB),"n"(HB));
}
template <int OA, uint32_t HA, int OB, uint32_t HB> __device__ __forceinline__ void mma_kv80(float* d, uint32_t a, uint32_t b) {
  asm volatile("{\n.reg .pred p;\nsetp.ne.b32 p, 1, 0;\n.reg .b32 ta, tb;\n.reg .b64 da, db;\nadd.u32 ta, %40, %42;\nmov.b64 da, {ta, %43};\nadd.u32 tb, %41, %44;\nmov.b64 db, {tb, %45};\n"
    "wgmma.mma_async.sync.aligned.m64n80k16.f32.bf16.bf16 {%0,%1,%2,%3,%4,%5,%6,%7,%8,%9,%10,%11,%12,%13,%14,%15,%16,%17,%18,%19,%20,%21,%22,%23,%24,%25,%26,%27,%28,%29,%30,%31,%32,%33,%34,%35,%36,%37,%38,%39}, da, db, p,1,1,1,1;\n}\n"
    : "+f"(d[0]),"+f"(d[1]),"+f"(d[2]),"+f"(d[3]),"+f"(d[4]),"+f"(d[5]),"+f"(d[6]),"+f"(d[7]),"+f"(d[8]),"+f"(d[9]),"+f"(d[10]),"+f"(d[11]),"+f"(d[12]),"+f"(d[13]),"+f"(d[14]),"+f"(d[15]),"+f"(d[16]),"+f"(d[17]),"+f"(d[18]),"+f"(d[19]),"+f"(d[20]),"+f"(d[21]),"+f"(d[22]),"+f"(d[23]),"+f"(d[24]),"+f"(d[25]),"+f"(d[26]),"+f"(d[27]),"+f"(d[28]),"+f"(d[29]),"+f"(d[30]),"+f"(d[31]),"+f"(d[32]),"+f"(d[33]),"+f"(d[34]),"+f"(d[35]),"+f"(d[36]),"+f"(d[37]),"+f"(d[38]),"+f"(d[39])
    : "r"(a),"r"(b),"n"(OA),"n"(HA),"n"(OB),"n"(HB));
}
template <int OA, uint32_t HA, int OB, uint32_t HB> __device__ __forceinline__ void mma_kv80_z(float* d, uint32_t a, uint32_t b) {
  asm volatile("{\n.reg .pred p;\nsetp.ne.b32 p, 0, 0;\n.reg .b32 ta, tb;\n.reg .b64 da, db;\nadd.u32 ta, %40, %42;\nmov.b64 da, {ta, %43};\nadd.u32 tb, %41, %44;\nmov.b64 db, {tb, %45};\n"
    "wgmma.mma_async.sync.aligned.m64n80k16.f32.bf16.bf16 {%0,%1,%2,%3,%4,%5,%6,%7,%8,%9,%10,%11,%12,%13,%14,%15,%16,%17,%18,%19,%20,%21,%22,%23,%24,%25,%26,%27,%28,%29,%30,%31,%32,%33,%34,%35,%36,%37,%38,%39}, da, db, p,1,1,1,1;\n}\n"
    : "=f"(d[0]),"=f"(d[1]),"=f"(d[2]),"=f"(d[3]),"=f"(d[4]),"=f"(d[5]),"=f"(d[6]),"=f"(d[7]),"=f"(d[8]),"=f"(d[9]),"=f"(d[10]),"=f"(d[11]),"=f"(d[12]),"=f"(d[13]),"=f"(d[14]),"=f"(d[15]),"=f"(d[16]),"=f"(d[17]),"=f"(d[18]),"=f"(d[19]),"=f"(d[20]),"=f"(d[21]),"=f"(d[22]),"=f"(d[23]),"=f"(d[24]),"=f"(d[25]),"=f"(d[26]),"=f"(d[27]),"=f"(d[28]),"=f"(d[29]),"=f"(d[30]),"=f"(d[31]),"=f"(d[32]),"=f"(d[33]),"=f"(d[34]),"=f"(d[35]),"=f"(d[36]),"=f"(d[37]),"=f"(d[38]),"=f"(d[39])
    : "r"(a),"r"(b),"n"(OA),"n"(HA),"n"(OB),"n"(HB));
}
template <int OB, uint32_t HB> __device__ __forceinline__ void mma_o88(float* d, uint32_t a0, uint32_t a1, uint32_t a2, uint32_t a3, uint32_t b) {
  asm volatile("{\n.reg .pred p;\nsetp.ne.b32 p, 1, 0;\n.reg .b32 tb;\n.reg .b64 db;\nadd.u32 tb, %48, %49;\nmov.b64 db, {tb, %50};\n"
    "wgmma.mma_async.sync.aligned.m64n88k16.f32.bf16.bf16 {%0,%1,%2,%3,%4,%5,%6,%7,%8,%9,%10,%11,%12,%13,%14,%15,%16,%17,%18,%19,%20,%21,%22,%23,%24,%25,%26,%27,%28,%29,%30,%31,%32,%33,%34,%35,%36,%37,%38,%39,%40,%41,%42,%43}, {%44,%45,%46,%47}, db, p,1,1,0;\n}\n"
    : "+f"(d[0]),"+f"(d[1]),"+f"(d[2]),"+f"(d[3]),"+f"(d[4]),"+f"(d[5]),"+f"(d[6]),"+f"(d[7]),"+f"(d[8]),"+f"(d[9]),"+f"(d[10]),"+f"(d[11]),"+f"(d[12]),"+f"(d[13]),"+f"(d[14]),"+f"(d[15]),"+f"(d[16]),"+f"(d[17]),"+f"(d[18]),"+f"(d[19]),"+f"(d[20]),"+f"(d[21]),"+f"(d[22]),"+f"(d[23]),"+f"(d[24]),"+f"(d[25]),"+f"(d[26]),"+f"(d[27]),"+f"(d[28]),"+f"(d[29]),"+f"(d[30]),"+f"(d[31]),"+f"(d[32]),"+f"(d[33]),"+f"(d[34]),"+f"(d[35]),"+f"(d[36]),"+f"(d[37]),"+f"(d[38]),"+f"(d[39]),"+f"(d[40]),"+f"(d[41]),"+f"(d[42]),"+f"(d[43])
    : "r"(a0),"r"(a1),"r"(a2),"r"(a3),"r"(b),"n"(OB),"n"(HB));
}
template <int OB, uint32_t HB> __device__ __forceinline__ void mma_o88_z(float* d, uint32_t a0, uint32_t a1, uint32_t a2, uint32_t a3, uint32_t b) {
  asm volatile("{\n.reg .pred p;\nsetp.ne.b32 p, 0, 0;\n.reg .b32 tb;\n.reg .b64 db;\nadd.u32 tb, %48, %49;\nmov.b64 db, {tb, %50};\n"
    "wgmma.mma_async.sync.aligned.m64n88k16.f32.bf16.bf16 {%0,%1,%2,%3,%4,%5,%6,%7,%8,%9,%10,%11,%12,%13,%14,%15,%16,%17,%18,%19,%20,%21,%22,%23,%24,%25,%26,%27,%28,%29,%30,%31,%32,%33,%34,%35,%36,%37,%38,%39,%40,%41,%42,%43}, {%44,%45,%46,%47}, db, p,1,1,0;\n}\n"
    : "=f"(d[0]),"=f"(d[1]),"=f"(d[2]),"=f"(d[3]),"=f"(d[4]),"=f"(d[5]),"=f"(d[6]),"=f"(d[7]),"=f"(d[8]),"=f"(d[9]),"=f"(d[10]),"=f"(d[11]),"=f"(d[12]),"=f"(d[13]),"=f"(d[14]),"=f"(d[15]),"=f"(d[16]),"=f"(d[17]),"=f"(d[18]),"=f"(d[19]),"=f"(d[20]),"=f"(d[21]),"=f"(d[22]),"=f"(d[23]),"=f"(d[24]),"=f"(d[25]),"=f"(d[26]),"=f"(d[27]),"=f"(d[28]),"=f"(d[29]),"=f"(d[30]),"=f"(d[31]),"=f"(d[32]),"=f"(d[33]),"=f"(d[34]),"=f"(d[35]),"=f"(d[36]),"=f"(d[37]),"=f"(d[38]),"=f"(d[39]),"=f"(d[40]),"=f"(d[41]),"=f"(d[42]),"=f"(d[43])
    : "r"(a0),"r"(a1),"r"(a2),"r"(a3),"r"(b),"n"(OB),"n"(HB));
}
template <int OA, uint32_t HA, int OB, uint32_t HB> __device__ __forceinline__ void mma_out80(float* d, uint32_t a, uint32_t b) {
  asm volatile("{\n.reg .pred p;\nsetp.ne.b32 p, 1, 0;\n.reg .b32 ta, tb;\n.reg .b64 da, db;\nadd.u32 ta, %40, %42;\nmov.b64 da, {ta, %43};\nadd.u32 tb, %41, %44;\nmov.b64 db, {tb, %45};\n"
    "wgmma.mma_async.sync.aligned.m64n80k16.f32.bf16.bf16 {%0,%1,%2,%3,%4,%5,%6,%7,%8,%9,%10,%11,%12,%13,%14,%15,%16,%17,%18,%19,%20,%21,%22,%23,%24,%25,%26,%27,%28,%29,%30,%31,%32,%33,%34,%35,%36,%37,%38,%39}, da, db, p,1,1,0,1;\n}\n"
    : "+f"(d[0]),"+f"(d[1]),"+f"(d[2]),"+f"(d[3]),"+f"(d[4]),"+f"(d[5]),"+f"(d[6]),"+f"(d[7]),"+f"(d[8]),"+f"(d[9]),"+f"(d[10]),"+f"(d[11]),"+f"(d[12]),"+f"(d[13]),"+f"(d[14]),"+f"(d[15]),"+f"(d[16]),"+f"(d[17]),"+f"(d[18]),"+f"(d[19]),"+f"(d[20]),"+f"(d[21]),"+f"(d[22]),"+f"(d[23]),"+f"(d[24]),"+f"(d[25]),"+f"(d[26]),"+f"(d[27]),"+f"(d[28]),"+f"(d[29]),"+f"(d[30]),"+f"(d[31]),"+f"(d[32]),"+f"(d[33]),"+f"(d[34]),"+f"(d[35]),"+f"(d[36]),"+f"(d[37]),"+f"(d[38]),"+f"(d[39])
    : "r"(a),"r"(b),"n"(OA),"n"(HA),"n"(OB),"n"(HB));
}
template <int OA, uint32_t HA, int OB, uint32_t HB> __device__ __forceinline__ void mma_kg24(float* d, uint32_t a, uint32_t b) {
  asm volatile("{\n.reg .pred p;\nsetp.ne.b32 p, 1, 0;\n.reg .b32 ta, tb;\n.reg .b64 da, db;\nadd.u32 ta, %12, %14;\nmov.b64 da, {ta, %15};\nadd.u32 tb, %13, %16;\nmov.b64 db, {tb, %17};\n"
    "wgmma.mma_async.sync.aligned.m64n24k16.f32.f16.f16 {%0,%1,%2,%3,%4,%5,%6,%7,%8,%9,%10,%11}, da, db, p,1,1,1,1;\n}\n"
    : "+f"(d[0]),"+f"(d[1]),"+f"(d[2]),"+f"(d[3]),"+f"(d[4]),"+f"(d[5]),"+f"(d[6]),"+f"(d[7]),"+f"(d[8]),"+f"(d[9]),"+f"(d[10]),"+f"(d[11])
    : "r"(a),"r"(b),"n"(OA),"n"(HA),"n"(OB),"n"(HB));
}
template <int OA, uint32_t HA, int OB, uint32_t HB> __device__ __forceinline__ void mma_kg24_z(float* d, uint32_t a, uint32_t b) {
  asm volatile("{\n.reg .pred p;\nsetp.ne.b32 p, 0, 0;\n.reg .b32 ta, tb;\n.reg .b64 da, db;\nadd.u32 ta, %12, %14;\nmov.b64 da, {ta, %15};\nadd.u32 tb, %13, %16;\nmov.b64 db, {tb, %17};\n"
    "wgmma.mma_async.sync.aligned.m64n24k16.f32.f16.f16 {%0,%1,%2,%3,%4,%5,%6,%7,%8,%9,%10,%11}, da, db, p,1,1,1,1;\n}\n"
    : "=f"(d[0]),"=f"(d[1]),"=f"(d[2]),"=f"(d[3]),"=f"(d[4]),"=f"(d[5]),"=f"(d[6]),"=f"(d[7]),"=f"(d[8]),"=f"(d[9]),"=f"(d[10]),"=f"(d[11])
    : "r"(a),"r"(b),"n"(OA),"n"(HA),"n"(OB),"n"(HB));
}
template <int OB, uint32_t HB> __device__ __forceinline__ void mma_cv128(float* d, uint32_t a0, uint32_t a1, uint32_t a2, uint32_t a3, uint32_t b) {
  asm volatile("{\n.reg .pred p;\nsetp.ne.b32 p, 1, 0;\n.reg .b32 tb;\n.reg .b64 db;\nadd.u32 tb, %68, %69;\nmov.b64 db, {tb, %70};\n"
    "wgmma.mma_async.sync.aligned.m64n128k16.f32.bf16.bf16 {%0,%1,%2,%3,%4,%5,%6,%7,%8,%9,%10,%11,%12,%13,%14,%15,%16,%17,%18,%19,%20,%21,%22,%23,%24,%25,%26,%27,%28,%29,%30,%31,%32,%33,%34,%35,%36,%37,%38,%39,%40,%41,%42,%43,%44,%45,%46,%47,%48,%49,%50,%51,%52,%53,%54,%55,%56,%57,%58,%59,%60,%61,%62,%63}, {%64,%65,%66,%67}, db, p,1,1,0;\n}\n"
    : "+f"(d[0]),"+f"(d[1]),"+f"(d[2]),"+f"(d[3]),"+f"(d[4]),"+f"(d[5]),"+f"(d[6]),"+f"(d[7]),"+f"(d[8]),"+f"(d[9]),"+f"(d[10]),"+f"(d[11]),"+f"(d[12]),"+f"(d[13]),"+f"(d[14]),"+f"(d[15]),"+f"(d[16]),"+f"(d[17]),"+f"(d[18]),"+f"(d[19]),"+f"(d[20]),"+f"(d[21]),"+f"(d[22]),"+f"(d[23]),"+f"(d[24]),"+f"(d[25]),"+f"(d[26]),"+f"(d[27]),"+f"(d[28]),"+f"(d[29]),"+f"(d[30]),"+f"(d[31]),"+f"(d[32]),"+f"(d[33]),"+f"(d[34]),"+f"(d[35]),"+f"(d[36]),"+f"(d[37]),"+f"(d[38]),"+f"(d[39]),"+f"(d[40]),"+f"(d[41]),"+f"(d[42]),"+f"(d[43]),"+f"(d[44]),"+f"(d[45]),"+f"(d[46]),"+f"(d[47]),"+f"(d[48]),"+f"(d[49]),"+f"(d[50]),"+f"(d[51]),"+f"(d[52]),"+f"(d[53]),"+f"(d[54]),"+f"(d[55]),"+f"(d[56]),"+f"(d[57]),"+f"(d[58]),"+f"(d[59]),"+f"(d[60]),"+f"(d[61]),"+f"(d[62]),"+f"(d[63])
    : "r"(a0),"r"(a1),"r"(a2),"r"(a3),"r"(b),"n"(OB),"n"(HB));
}
template <int OB, uint32_t HB> __device__ __forceinline__ void mma_cv128_z(float* d, uint32_t a0, uint32_t a1, uint32_t a2, uint32_t a3, uint32_t b) {
  asm volatile("{\n.reg .pred p;\nsetp.ne.b32 p, 0, 0;\n.reg .b32 tb;\n.reg .b64 db;\nadd.u32 tb, %68, %69;\nmov.b64 db, {tb, %70};\n"
    "wgmma.mma_async.sync.aligned.m64n128k16.f32.bf16.bf16 {%0,%1,%2,%3,%4,%5,%6,%7,%8,%9,%10,%11,%12,%13,%14,%15,%16,%17,%18,%19,%20,%21,%22,%23,%24,%25,%26,%27,%28,%29,%30,%31,%32,%33,%34,%35,%36,%37,%38,%39,%40,%41,%42,%43,%44,%45,%46,%47,%48,%49,%50,%51,%52,%53,%54,%55,%56,%57,%58,%59,%60,%61,%62,%63}, {%64,%65,%66,%67}, db, p,1,1,0;\n}\n"
    : "=f"(d[0]),"=f"(d[1]),"=f"(d[2]),"=f"(d[3]),"=f"(d[4]),"=f"(d[5]),"=f"(d[6]),"=f"(d[7]),"=f"(d[8]),"=f"(d[9]),"=f"(d[10]),"=f"(d[11]),"=f"(d[12]),"=f"(d[13]),"=f"(d[14]),"=f"(d[15]),"=f"(d[16]),"=f"(d[17]),"=f"(d[18]),"=f"(d[19]),"=f"(d[20]),"=f"(d[21]),"=f"(d[22]),"=f"(d[23]),"=f"(d[24]),"=f"(d[25]),"=f"(d[26]),"=f"(d[27]),"=f"(d[28]),"=f"(d[29]),"=f"(d[30]),"=f"(d[31]),"=f"(d[32]),"=f"(d[33]),"=f"(d[34]),"=f"(d[35]),"=f"(d[36]),"=f"(d[37]),"=f"(d[38]),"=f"(d[39]),"=f"(d[40]),"=f"(d[41]),"=f"(d[42]),"=f"(d[43]),"=f"(d[44]),"=f"(d[45]),"=f"(d[46]),"=f"(d[47]),"=f"(d[48]),"=f"(d[49]),"=f"(d[50]),"=f"(d[51]),"=f"(d[52]),"=f"(d[53]),"=f"(d[54]),"=f"(d[55]),"=f"(d[56]),"=f"(d[57]),"=f"(d[58]),"=f"(d[59]),"=f"(d[60]),"=f"(d[61]),"=f"(d[62]),"=f"(d[63])
    : "r"(a0),"r"(a1),"r"(a2),"r"(a3),"r"(b),"n"(OB),"n"(HB));
}

template <int H>
__device__ __forceinline__ void dual_softmax(const float* acc, uint32_t* out) {
  constexpr float L2E = 1.4426950408889634f;
  float mx = fmaxf(acc[2 * H], acc[2 * H + 1]), mn = fminf(acc[2 * H], acc[2 * H + 1]);
#pragma unroll
  for (int b = 1; b < 10; b++) {
    mx = fmaxf(mx, fmaxf(acc[4 * b + 2 * H], acc[4 * b + 2 * H + 1]));
    mn = fminf(mn, fminf(acc[4 * b + 2 * H], acc[4 * b + 2 * H + 1]));
  }
  const float mxl = -mx * L2E, mnl = mn * L2E;
#pragma unroll
  for (int half = 0; half < 2; half++) {
    float e[20];
    float s0 = 0.f, s1 = 0.f;
#pragma unroll
    for (int i = 0; i < 10; i++) {
      const float p0 = acc[4 * i + 2 * H], p1 = acc[4 * i + 2 * H + 1];
      e[2 * i] = ex2(half ? fmaf(p0, -L2E, mnl) : fmaf(p0, L2E, mxl));
      e[2 * i + 1] = ex2(half ? fmaf(p1, -L2E, mnl) : fmaf(p1, L2E, mxl));
      s0 += e[2 * i];
      s1 += e[2 * i + 1];
    }
    const float r = rcp(s0 + s1);
#pragma unroll
    for (int i = 0; i < 10; i++) out[10 * half + i] = pack_bf16(e[2 * i] * r, e[2 * i + 1] * r);
  }
}

struct Cx { float re, im; };
__device__ __forceinline__ Cx cmul(Cx a, Cx b) { return Cx{fmaf(a.re, b.re, -a.im * b.im), fmaf(a.re, b.im, a.im * b.re)}; }
__device__ __forceinline__ Cx cexp_e(float za, float zi, float e) {
  const float m = ex2(za * e);
  const float ph = zi * e;
  const float k = __fadd_rn(__fmaf_rn(ph, 0.15915494f, 12582912.f), -12582912.f);
  float r = fmaf(ph, 0.15915494f, -k);
  r = fmaf(ph, 6.4206382e-9f, r);
  r *= 6.2831853071795865f;
  return Cx{m * __cosf(r), m * __sinf(r)};
}

__device__ __forceinline__ Cx csqr(Cx a) { return Cx{fmaf(a.re, a.re, -a.im * a.im), (a.re + a.re) * a.im}; }
struct Hp { uint32_t re, im; };
__device__ __forceinline__ Hp planar(Cx a, Cx b) { return Hp{pack_f16(a.re, b.re), pack_f16(a.im, b.im)}; }
__device__ __forceinline__ Hp hpmul(Hp x, uint32_t y) {
  const __half2 Y = *reinterpret_cast<const __half2*>(&y), R = *reinterpret_cast<const __half2*>(&x.re), I = *reinterpret_cast<const __half2*>(&x.im);
  const __half2 r = __hfma2(__hneg2(I), __high2half2(Y), __hmul2(R, __low2half2(Y)));
  const __half2 i = __hfma2(R, __high2half2(Y), __hmul2(I, __low2half2(Y)));
  return Hp{*reinterpret_cast<const uint32_t*>(&r), *reinterpret_cast<const uint32_t*>(&i)};
}

struct Anchors { Hp e[4], b4, b8, b16, xa, xb; uint32_t b2, y[8]; };
__device__ __forceinline__ void ssm_anchors(float za, float zi, Cx cs, Anchors& a) {
  const Cx e1 = cexp_e(za, -zi, 1.f), b2 = cexp_e(za, -zi, 256.f), x1 = cexp_e(za, zi, 8.f);
  const Cx e2 = csqr(e1), e3 = cmul(e2, e1), e4 = csqr(e2), e5 = cmul(e4, e1), e6 = csqr(e3), e7 = cmul(e4, e3);
  const Cx b4 = csqr(b2), b8 = csqr(b4), b12 = cmul(b8, b4), b16 = csqr(b8), b4e = cmul(b4, e4);
  a.e[0] = planar(Cx{1.f, 0.f}, e2); a.e[1] = planar(e4, e6); a.e[2] = planar(e1, e3); a.e[3] = planar(e5, e7);
  a.b2 = pack_f16(b2.re, b2.im); a.b4 = planar(b4, b4e); a.b8 = planar(b8, b12); a.b16 = planar(b16, Cx{0.f, 0.f});
  const Cx x2 = csqr(x1), x3 = cmul(x2, x1), x4 = csqr(x2);
  a.xa = planar(Cx{1.f, 0.f}, x1);
  a.xb = planar(x2, x3);
  Cx y = cs;
#pragma unroll
  for (int j = 0; j < 8; j++) {
    a.y[j] = pack_f16(y.re, y.im);
    if (j < 7) y = cmul(y, x4);
  }
}
__device__ __forceinline__ void store_factors(const Anchors& a, uint32_t tab, int t) {
  const uint32_t ar = tab + (t >> 2) * 128 + (t & 4) * 16 + (t & 3) * 16, ai = ar ^ 64;
  auto put = [&](int i, Hp v0, Hp v1, Hp v2, Hp v3) {
    sts128(ar + i * 4096, v0.re, v1.re, v2.re, v3.re);
    sts128(ai + i * 4096, v0.im, v1.im, v2.im, v3.im);
  };
  put(4, a.e[0], a.e[1], a.e[2], a.e[3]);
  put(5, hpmul(a.e[0], a.b2), hpmul(a.e[1], a.b2), a.b4, hpmul(a.b4, a.b2));
  put(6, a.b8, hpmul(a.b8, a.b2), a.b16, Hp{0u, 0u});
#pragma unroll
  for (int i = 0; i < 4; i++) put(i, hpmul(a.xa, a.y[2 * i]), hpmul(a.xb, a.y[2 * i]), hpmul(a.xa, a.y[2 * i + 1]), hpmul(a.xb, a.y[2 * i + 1]));
  fence_async_smem();
}
__device__ __forceinline__ void ssm_gemm(float* kd, uint32_t tab) {
  const uint32_t d = dlo(tab, 128);
  constexpr uint32_t H = dhi(4096, 0);
  mma_kg24_z<0, H, 1024, H>(kd, d, d);
  static_for<1, 16>([&](auto k) { mma_kg24<k * 16, H, 1024 + k * 16, H>(kd, d, d); });
  wg_commit();
}

__device__ __forceinline__ void store_taps(const float* kd, float unscale, float dskip, uint32_t kz, int t) {
  if (t < 64) {
    const int q = t & 3, i = (t >> 5) * 16 + ((t & 31) >> 2);
    const bool lo = q < 2;
    const uint32_t a0 = kz + (8 * i + 4 * (q & 1) + (q >> 1)) * 2, a1 = kz + 512 + (lo ? 8 * i + 4 * q : 128 * q + 4 * i);
    const uint32_t a2 = kz + (lo ? 1024 + 64 * q + 2 * i : 1284), a3 = kz + (lo ? 1152 + 64 * q + 2 * i : 1284);
#pragma unroll
    for (int h = 0; h < 2; h++) {
      const uint32_t w0 = pack_bf16(fmaf(kd[2 * h], unscale, (h == 0 && t == 0) ? dskip : 0.f), kd[2 * h + 1] * unscale);
      const uint32_t w2 = pack_bf16(kd[8 + 2 * h] * unscale, kd[9 + 2 * h] * unscale);
      sts16(a0 + 128 * h, w0 & 0xffffu);
      sts16(a0 + 128 * h + 4, w0 >> 16);
      sts32(a1 + (h ? (lo ? 64 : 32) : 0), pack_bf16(kd[4 + 2 * h] * unscale, kd[5 + 2 * h] * unscale));
      sts16(h ? a2 + (lo ? 16 : 0) : t == 2 ? kz + 1280 : a2, w2 & 0xffffu);
      sts16(h ? a3 + (lo ? 16 : 0) : a3, w2 >> 16);
    }
  }
}

template <int N>
__device__ __forceinline__ void build_taps(uint32_t kz, uint32_t pt, uint32_t hh, int t0, int step) {
  uint32_t w[N], wm[N], v0[N], vm[N], vp[N], a[N][2], b[N][2];
#pragma unroll
  for (int n = 0; n < N; n++) {
    const int t = t0 + n * step, odd = t & 1;
    w[n] = lds32(kz + t * 4);
    wm[n] = lds16(kz + t * 4 - (t ? 2 : 0));
    v0[n] = lds16(kz + (256 + t) * 2);
    vm[n] = lds16(kz + (256 + t - odd) * 2);
    vp[n] = lds16(kz + (256 + t + odd) * 2);
#pragma unroll
    for (int i = 0; i < 2; i++) {
      a[n][i] = lds16(kz + (384 + 64 * i + (t >> 1)) * 2);
      b[n][i] = lds16(kz + (385 + 64 * i + (t >> 1)) * 2);
    }
  }
  uint32_t s = 0, k0 = 0, k1 = 0, k2 = 0;
  if (t0 < 3) { s = lds16(kz + 1024); k0 = lds16(kz + 510); k1 = lds16(kz + 768); k2 = lds16(kz + 896); }
#pragma unroll
  for (int n = 0; n < N; n++) {
    const int t = t0 + n * step;
    const uint32_t hi_mask = t ? 0xffffffffu : 0x0000ffffu;
    sts128(pt + 128 + t * 16, __byte_perm(w[n], wm[n], 0x5410) & hi_mask, __byte_perm(v0[n], vm[n], 0x5410) & hi_mask,
           __byte_perm(w[n], w[n], 0x1032), __byte_perm(vp[n], v0[n], 0x5410));
    uint32_t t0w[2], t1w[2];
#pragma unroll
    for (int i = 0; i < 2; i++) {
      const uint32_t mid = (t & 3) == 3 ? b[n][i] : a[n][i], hi = (t & 1) ? b[n][i] : a[n][i];
      t0w[i] = __byte_perm(mid, a[n][i], 0x5410) & hi_mask;
      t1w[i] = __byte_perm(hi, mid, 0x5410);
    }
    sts128(pt + 2432 + 128 + t * 16, t0w[0], t0w[1], t1w[0], t1w[1]);
  }
  if (t0 < 3) {
    const uint32_t ss = s | (s << 16);
    if (t0 == 0) sts64(pt + 128 + 2048, k0 << 16, k1 << 16);
    sts128(pt + 2432 + 128 + 2048 + t0 * 16, t0 ? 0u : k2 << 16, ss, 0u, t0 == 2 ? s << 16 : ss);
  }
  uint32_t hv[N][8];
#pragma unroll
  for (int n = 0; n < N; n++) {
    const int t = t0 + n * step, om = t & 63;
    const uint32_t hb = kz + (513 + (t >> 6) + 2 * om) * 2;
#pragma unroll
    for (int i = 0; i < 8; i++) hv[n][i] = lds16(hb - 4 * i);
  }
#pragma unroll
  for (int n = 0; n < N; n++) {
    const int t = t0 + n * step, om = t & 63;
    uint32_t o[4];
#pragma unroll
    for (int i = 0; i < 4; i++) o[i] = om > 2 * i ? __byte_perm(hv[n][2 * i], hv[n][2 * i + 1], 0x5410) : om == 2 * i ? hv[n][2 * i] : 0u;
    sts128(hh + (t >> 6) * 2176 + (72 + om) * 16, o[0], o[1], o[2], o[3]);
  }
}

__device__ __forceinline__ void build_windows(uint32_t ub, uint32_t wdst, int t) {
  float p[24];
#pragma unroll
  for (int c = 0; c < 4; c++) {
    const int chi = t - 3 + c + 2 * UB_Z;
    const uint4 v = lds128(ub + (chi & 1) * UB_C + (chi >> 1) * 16);
    const uint32_t w[4] = {v.x, v.y, v.z, v.w};
#pragma unroll
    for (int e = 0; e < 8; e++) {
      const int i = 8 * c + e - 3;
      if (i >= 1 && i < 24) p[i] = (e & 1) ? __uint_as_float(w[e >> 1] & 0xffff0000u) : __uint_as_float(w[e >> 1] << 16);
    }
  }
  p[0] = 0.f;
#pragma unroll
  for (int i = 1; i < 8; i++) { if (i > 1) p[i] += p[i - 1]; p[8 + i] += p[7 + i]; p[16 + i] += p[15 + i]; }
  const float c1 = p[7], c2 = p[7] + p[15];
#pragma unroll
  for (int i = 8; i < 16; i++) { p[i] += c1; p[8 + i] += c2; }
  uint32_t o[4], e[4];
#pragma unroll
  for (int i = 0; i < 4; i++) {
    e[i] = pack_bf16(p[2 * i + 9] - p[2 * i], p[2 * i + 10] - p[2 * i + 1]);
    o[i] = pack_bf16(p[2 * i + 16] - p[2 * i + 9], p[2 * i + 17] - p[2 * i + 10]);
  }
  const uint32_t a = wdst + (t ^ ((t >> 3) & 1)) * 16;
  sts128(a, o[0], o[1], o[2], o[3]);
  sts128(a + 2048, e[0], e[1], e[2], e[3]);
}

__device__ __forceinline__ void ldsm4t(uint32_t* r, uint32_t a) {
  asm volatile("ldmatrix.sync.aligned.m8n8.x4.trans.shared.b16 {%0,%1,%2,%3}, [%4];" : "=r"(r[0]), "=r"(r[1]), "=r"(r[2]), "=r"(r[3]) : "r"(a) : "memory");
}
__device__ __forceinline__ void load_frag(uint32_t* r, uint32_t a) {
  const uint2 x = lds64(a), y = lds64(a - 64);
  r[0] = x.x; r[1] = x.y; r[2] = y.x; r[3] = y.y;
}

__device__ __forceinline__ void transpose_store(const uint4* L, uint4* dst, int stride) {
  dst[0] = make_uint4(movm(L[0].x), movm(L[1].x), movm(L[2].x), movm(L[3].x));
  dst[stride] = make_uint4(movm(L[0].y), movm(L[1].y), movm(L[2].y), movm(L[3].y));
  dst[2 * stride] = make_uint4(movm(L[0].z), movm(L[1].z), movm(L[2].z), movm(L[3].z));
  dst[3 * stride] = make_uint4(movm(L[0].w), movm(L[1].w), movm(L[2].w), movm(L[3].w));
}

#define LANE_IDS                                           \
  int tid_;                                                \
  asm volatile("mov.u32 %0, %%tid.x;" : "=r"(tid_));       \
  tid_ = (tid_ + ROT) & 511;                               \
  const int lane = tid_ & 31, wp = (tid_ >> 5) & 3, g = lane >> 2, q = lane & 3; \
  (void)wp; (void)g; (void)q;
#define ROW_IDS LANE_IDS const int row = (tid_ >> 5) * 16 + g;

__global__ void __launch_bounds__(512, 1) fused_kernel(const __grid_constant__ Params P) {
  extern __shared__ __align__(1024) uint8_t smem_raw[];
  const uint32_t sb = (uint32_t)__cvta_generic_to_shared(smem_raw);
  const int tid = (threadIdx.x + ROT) & 511;
  unsigned smid;
  asm("mov.u32 %0, %%smid;" : "=r"(smid));
  const int cta = P.tile_of_sm[smid < 192 ? smid : 191];
  if (cta >= NCTA) {
    if (tid == 0) wait_count(CNT_START, (atomicAdd(&g_cnt[CNT_START * 32], 1u) / P.nsm + 1) * P.nsm);
    return;
  }
  const int rb = cta >> 3;
  const int hg = cta & 7;

  if (tid == 384) {
    mbar_init(sb + BAR_FULL, 1);
    asm volatile("fence.mbarrier_init.release.cluster;" ::: "memory");
    mbar_expect(sb + BAR_FULL, STAGE);
    tma2d(sb, &P.x, sb + BAR_FULL, 0, rb * 128);
    tma3d(sb + OFF_W128, &P.w128, sb + BAR_FULL, hg * 80, 0, 0);
    tma3d(sb + OFF_W16, &P.w16, sb + BAR_FULL, hg * 80 + 64, 0, 0);
    STAMP(46);
  } else if ((tid & 31) == 0 && (tid < 256 || tid > 384)) {
    const int w = tid < 256 ? tid >> 5 : (tid >> 5) - 5;
#pragma unroll
    for (int i = 0; i < 3; i++) mbar_init(sb + SM_MISC + 8 * (1 + 3 * w + i), P.bar_count[1 + 3 * w + i]);
    if (w == 10) mbar_init(sb + BAR_KVB, 1);
    asm volatile("fence.mbarrier_init.release.cluster;" ::: "memory");
  }
  uint32_t raw[3][6], rawc = 0;
  if (tid >= 256 && tid < 384) {
#pragma unroll
    for (int c = 0; c < 2; c++)
#pragma unroll
      for (int i = 0; i < 6; i++) raw[c][i] = __ldg(P.ssm[i] + cta * 640 + c * 128 + tid - 256);
    const int l = tid & 31;
    if (l < 10) rawc = __ldg((l < 5 ? P.logdt : P.dskip - 5) + cta * 5 + l);
  }
  __syncthreads();

  if (tid >= 384) {
    asm volatile("setmaxnreg.dec.sync.aligned.u32 56;");
    LANE_IDS
    if (wp == 0) {
      if (lane == 0) {
        STAMP(40);
        for (int it = 1; it < 10; it++) {
          const int s = it & 3;
          if (it >= 4) mbar_wait(sb + BAR_EMPTY + 8 * s, ((it >> 2) - 1) & 1);
          const uint32_t d = sb + s * STAGE, fb = sb + BAR_FULL + 8 * s;
          mbar_expect(fb, STAGE);
          tma2d(d, &P.x, fb, it * 64, rb * 128);
          tma3d(d + OFF_W128, &P.w128, fb, hg * 80, it * 64, 0);
          tma3d(d + OFF_W16, &P.w16, fb, hg * 80 + 64, it * 64, 0);
          if (it == 3) {
            mbar_expect(sb + BAR_PRM, 4608);
            for (int i = 0; i < 6; i++)
              asm volatile("cp.async.bulk.shared::cluster.global.mbarrier::complete_tx::bytes [%0], [%1], 768, [%2];" ::"r"(sb + SM_UB0 + i * 768), "l"(P.ssm[i] + cta * 640 + 256), "r"(sb + BAR_PRM) : "memory");
            mbar_expect(sb + BAR_WP, 3200);
            asm volatile("cp.async.bulk.shared::cluster.global.mbarrier::complete_tx::bytes [%0], [%1], 3200, [%2];" ::"r"(sb + SM_WP), "l"(P.wphi + hg * 800), "r"(sb + BAR_WP) : "memory");
          }
        }
        mbar_expect(sb + BAR_WO, 102400);
        for (int j = 0; j < 7; j++) {
          if (j == 0) mbar_wait(sb + WO_FIRST, 0);
          if (j == 4) mbar_wait(sb + BAR_MAIN, 0);
          if (j == 5) mbar_wait(sb + BAR_PHI, 0);
          const int i = j < 4 ? j + 6 : j == 4 ? 0 : j - 1;
          tma3d(sb + SM_WO + i * 10240, &P.wo, sb + BAR_WO, 0, i * 64, hg * 5);
        }
        mbar_wait(sb + BAR_EPOCH, 0);
      }
      __syncwarp();
      const unsigned epoch = lds32(sb + SM_EPOCH);
      bar_sync<4, 288>();
      if (lane == 0) {
        asm volatile("cp.reduce.async.bulk.global.shared::cta.bulk_group.add.f32 [%0], [%1], 14400;" ::"l"(g_kv + (epoch & 1) * 28800 + hg * 3600), "r"(sb + SM_KVST) : "memory");
        bulk_commit_wait();
        STAMP(42);
        signal(CNT_KV + hg);
        STAMP(43);
        mbar_wait(sb + BAR_KGD, 0);
        mbar_wait(sb + BAR_KVB, 0);
        for (int i = 1; i < 4; i++) tma3d(sb + SM_WO + i * 10240, &P.wo, sb + BAR_WO, 0, i * 64, hg * 5);
      }
      __syncwarp();
      bar_sync<5, 288>();
      if (lane == 0) {
        tma2d_store(&P.ost, sb + SM_OST, hg * 80, rb * 128);
        bulk_commit_wait();
        STAMP(44);
        signal(CNT_O + rb);
        STAMP(45);
        wait_count(CNT_O + rb, (epoch + 1) * 8);
        fence_async_global();
        STAMP(41);
        for (int it = 0; it < 10; it++) {
          const int s = it < 5 ? it : it - 5;
          if (it >= 5) mbar_wait(sb + BAR_OEMPTY + 8 * s, 0);
          mbar_expect(sb + BAR_OFULL + 8 * s, 16384);
          tma2d(sb + (s < 4 ? s * 16384 : SM_O4), &P.o, sb + BAR_OFULL + 8 * s, it * 64, rb * 128);
        }
      }
    } else {
      const int ht = tid_ - 416;
      if (wp == 3 && lane < 5) asm volatile("prefetch.tensormap [%0];" ::"l"(&P.wo + lane) : "memory");
      if (wp == 1) {
        unsigned epoch = 0;
        if (lane == 0) {
          epoch = atomicAdd(&g_cnt[CNT_START * 32], 1u) / P.nsm;
          sts32(sb + SM_EPOCH, epoch);
          mbar_arrive(sb + BAR_EPOCH);
        }
        epoch = __shfl_sync(0xffffffffu, epoch, 0);
        float4* z = reinterpret_cast<float4*>(g_kv + ((epoch + 1) & 1) * 28800 + hg * 3600);
        for (int i = rb * 57 + lane; i < min(rb * 57 + 57, 900); i += 32) z[i] = make_float4(0.f, 0.f, 0.f, 0.f);
      }
      mbar_wait(sb + BAR_FULL, 0);
      {
        const int r0 = 64 * (cta & 31), c0 = 160 * (cta >> 5) + 32 * (wp - 1), gr = 8 * (g >> 1) + (g & 1);
        const uint4* src = reinterpret_cast<const uint4*>(P.u + (r0 + gr) * 640 + c0 + 8 * q);
        uint4* dst = reinterpret_cast<uint4*>(g_uT + (c0 + gr) * 2048 + r0 + 8 * q);
#pragma unroll 1
        for (int hi = 0; hi < 2; hi++, src += 2560, dst += 4) {
          uint4 L0[4], L1[4];
#pragma unroll
          for (int j = 0; j < 4; j++) L0[j] = __ldg(src + j * 160);
          if (wp < 3) {
#pragma unroll
            for (int j = 0; j < 4; j++) L1[j] = __ldg(src + j * 160 + 12);
          }
          transpose_store(L0, dst, 512);
          if (wp < 3) transpose_store(L1, dst + 96 * 256, 512);
        }
      }
      if (wp == 2) {
        bar_sync<6, 96>();
        STAMP_IF(lane == 0, 49);
        if (lane == 0) {
          signal(CNT_T1 + (cta >> 5));
          STAMP(47);
          mbar_wait(sb + BAR_EPOCH, 0);
          wait_count(CNT_T1 + (cta >> 5), (lds32(sb + SM_EPOCH) + 1) * 32);
          fence_async_global();
          STAMP(36);
          mbar_wait(sb + BAR_PRF, 0);
          mbar_expect(sb + BAR_UB, 2 * UB_C);
          tma4d(sb + SM_UB0, &P.ut, sb + BAR_UB, 0, -(int)UB_Z, 0, cta * 5);
        }
        __syncwarp();
      } else {
        bar_arrive<6, 96>();
        mbar_wait(sb + BAR_WP, 0);
        const int t = lane + 16 * (wp - 1);
        uint32_t w[13];
#pragma unroll
        for (int i = 0; i < 13; i++) {
          const int idx = min(t + 64 * i, 799), b = idx / 80;
          w[i] = lds32(sb + SM_WP + ((idx - 80 * b) * 10 + b) * 4);
        }
        mbar_wait(sb + BAR_S6, 0);
#pragma unroll
        for (int i = 0; i < 13; i++) {
          const int idx = t + 64 * i, j = (idx % 80) / 20;
          if (idx < 800) sts128(sb + SM_WPHI + idx * 16, j == 0 ? w[i] : 0u, j == 1 ? w[i] : 0u, j == 2 ? w[i] : 0u, j == 3 ? w[i] : 0u);
        }
        STAMP_IF(ht == 0, 48);
        bar_arrive<3, 320>();
      }
      mbar_wait(sb + BAR_MAIN, 0);
      mbar_wait(sb + BAR_K0, 0);
      for (int i = ht; i < 192; i += 96) {
        const uint32_t a = i < 48 ? SM_PT0 + (i / 24) * 2432 + (i % 24) * 16 + ((i % 24) >= 8 ? 2048 : 0) : SM_H + (i >= 120 ? 1024 : 0) + (i - 48) * 16;
        sts128(sb + a, 0u, 0u, 0u, 0u);
      }
      bar_sync<12, 96>();
      {
#pragma unroll 1
        for (int c = 0; c < 5; c++) {
          if (c > 0) mbar_wait(sb + BAR_FREE, (c - 1) & 1);
          if (wp == 1) {
            if (c == 1) {
              for (int i = lane; i < 48; i += 32) sts128(sb + SM_PT1 + (i / 24) * 2432 + (i % 24) * 16 + ((i % 24) >= 8 ? 2048 : 0), 0u, 0u, 0u, 0u);
              __syncwarp();
            }
#pragma unroll 1
            for (int tt = lane; tt < 128; tt += 64) build_taps<2>(sb + SM_KZ + c * 1296, sb + ((c & 1) ? SM_PT1 : SM_PT0), sb + SM_H, tt, 32);
          } else {
            mbar_wait(sb + BAR_UB + 8 * (c & 1), (c >> 1) & 1);
#pragma unroll 1
            for (int tt = ht - 32; tt < 128; tt += 64) build_windows(sb + ((c & 1) ? SM_UB1 : SM_UB0), sb + SM_W, tt);
          }
          fence_async_smem();
          mbar_arrive(sb + BAR_RDY);
          if (c == 0 && ht == 32) {
            mbar_wait(sb + BAR_KGD, 0);
            mbar_expect(sb + BAR_UB + 8, 2 * UB_C);
            tma4d(sb + SM_UB1, &P.ut, sb + BAR_UB + 8, 0, -(int)UB_Z, 0, cta * 5 + 1);
          }
          __syncwarp();
          STAMP_IF(lane == 0 && c == 1 && wp < 3, 49 + wp);
        }
      }
    }
  } else if (tid >= 256) {
    asm volatile("setmaxnreg.dec.sync.aligned.u32 120;");
    LANE_IDS
    const int bt = tid_ - 256;
    const int grp = cta >> 5, gi = cta & 31;
    const int ch0 = cta * 5;
    {
      uint32_t pa[3], pc[3], pex = 0;
      const uint32_t dtl = __bfloat16_as_ushort(__float2bfloat16_rn(expf(bf2f(rawc))));
      auto prep = [&](auto nc, int c0) {
        constexpr int N = nc;
        Cx cc[N];
#pragma unroll
        for (int c = 0; c < N; c++) {
          const float dt = bf2f(__shfl_sync(0xffffffffu, dtl, c0 + c));
          pa[c] = raw[c][0] | (raw[c][1] << 16);
          cc[c] = cmul(Cx{bf2f(raw[c][4]), bf2f(raw[c][5])}, Cx{dt * bf2f(raw[c][2]), dt * bf2f(raw[c][3])});
          const unsigned m = __reduce_max_sync(0xffffffffu, __float_as_uint(fmaxf(fabsf(cc[c].re), fabsf(cc[c].im))));
          if (lane == 0) sts32(sb + SM_CMAX + (c0 + c) * 16 + wp * 4, m);
        }
        bar_sync<2, 128>();
#pragma unroll
        for (int c = 0; c < N; c++) {
          const uint4 m4 = lds128(sb + SM_CMAX + (c0 + c) * 16);
          const unsigned ex = min(max(max(max(m4.x, m4.y), max(m4.z, m4.w)) >> 23, 1u), 253u) << 23;
          const float scale = __uint_as_float((254u << 23) - ex);
          pc[c] = pack_f16(cc[c].re * scale, cc[c].im * scale);
          if (lane == c0 + c) pex = ex;
        }
      };
      pa[2] = pc[2] = 0u;
      prep(IC<2>{}, 0);
      auto taps = [&](float* kd, int c) {
        store_taps(kd, __uint_as_float(__shfl_sync(0xffffffffu, pex, c)), __uint_as_float(__shfl_sync(0xffffffffu, rawc, 5 + c) << 16), sb + SM_KZ + c * 1296, bt);
      };
      Anchors a, held;
#pragma unroll
      for (int i = 0; i < 27; i++) reinterpret_cast<uint32_t*>(&a)[i] = 0u;
#pragma unroll 1
      for (int c = 0; c < 5; c++) {
        held = a;
        {
          const float dt = bf2f(__shfl_sync(0xffffffffu, dtl, c));
          const float2 cs = __half22float2(*reinterpret_cast<const __half2*>(&pc[0]));
          ssm_anchors(dt * bf2f(pa[0]) * 1.4426950408889634f, dt * __uint_as_float(pa[0] & 0xffff0000u), Cx{cs.x, cs.y}, a);
        }
#pragma unroll
        for (int i = 0; i < 2; i++) { pa[i] = pa[i + 1]; pc[i] = pc[i + 1]; }
        if (c == 1) {
          float kd[12];
          wg_fence();
          ssm_gemm(kd, sb + SM_KG);
          wg_wait<0>();
          pin<12>(kd);
          taps(kd, 0);
          mbar_arrive(sb + BAR_K0);
          mbar_wait(sb + BAR_PRM, 0);
#pragma unroll
          for (int k = 0; k < 3; k++)
#pragma unroll
            for (int i = 0; i < 6; i++) raw[k][i] = lds16(sb + SM_UB0 + i * 768 + k * 256 + bt * 2);
          prep(IC<3>{}, 2);
          fence_async_smem();
          mbar_arrive(sb + BAR_PRF);
        }
        if (c == 2) mbar_wait(sb + BAR_S6, 0);
        if (c < 3) {
          store_factors(a, sb + (c == 2 ? SM_KG2 : SM_KG), bt);
          bar_sync<2, 128>();
        }
        STAMP_IF(bt == 0, c == 1 ? 38 : 21 + c);
      }
      mbar_wait(sb + BAR_MAIN, 0);
      STAMP_IF(bt == 0, 37);
#pragma unroll 1
      for (int c = 1; c < 5; c += 2) {
        float k0[12], k1[12];
        wg_fence();
        ssm_gemm(k0, sb + SM_KG);
        ssm_gemm(k1, sb + SM_KG2);
        wg_wait<1>();
        pin<12>(k0);
        taps(k0, c);
        wg_wait<0>();
        pin<12>(k1);
        if (c == 3) mbar_arrive(sb + BAR_KGD);
        taps(k1, c + 1);
        if (c == 1) {
          bar_sync<2, 128>();
          pin<27>(reinterpret_cast<uint32_t*>(&held));
          store_factors(held, sb + SM_KG, bt);
          pin<27>(reinterpret_cast<uint32_t*>(&a));
          store_factors(a, sb + SM_KG2, bt);
          bar_sync<2, 128>();
        }
        STAMP_IF(bt == 0 && c == 1, 39);
      }
    }
    STAMP_IF(bt == 0, 22);
    mbar_wait(sb + BAR_EPOCH, 0);
    const unsigned epoch = lds32(sb + SM_EPOCH);
    const int r = wp >> 1, p = wp & 1;
#pragma unroll 1
    for (int c = 0; c < 5; c++) {
      const uint32_t ub = sb + ((c & 1) ? SM_UB1 : SM_UB0);
      mbar_wait(sb + BAR_RDY, c & 1);
      STAMP_IF(bt == 0 && c == 0, 33);
      mbar_wait(sb + BAR_UB + 8 * (c & 1), (c >> 1) & 1);
      STAMP_IF(bt == 0 && c == 1, 34);
      float y[64];
      uint32_t fr[4][4];
      const uint32_t wa = sb + SM_W + (32 * p + 8 - (lane >> 4) * 8 + ((lane >> 3) & 1) * 16 + (lane & 7)) * 32 + (r ^ ((lane >> 2) & 1)) * 16;
      const uint32_t pa = sb + ((c & 1) ? SM_PT1 : SM_PT0) + p * 2432 + (16 + 8 * r + g - 2 * q) * 8;
      const uint32_t dU = dlo(ub, UB_C), dH = dlo(sb + SM_H, 128);
      constexpr uint32_t HC = dhi(128, 0);
      ldsm4t(fr[2], wa);
      ldsm4t(fr[3], wa + 2048);
      load_frag(fr[0], pa);
      load_frag(fr[1], pa + 128);
      wg_fence();
      mma_cv128_z<0, HC>(y, fr[2][0], fr[2][1], fr[2][2], fr[2][3], dH);
      wg_commit();
      mma_cv128<136, HC>(y, fr[3][0], fr[3][1], fr[3][2], fr[3][3], dH);
      wg_commit();
      static_for<0, 18>([&](auto jc) {
        constexpr int j = jc;
        uint32_t* f = fr[j & 3];
        wg_fence();
        mma_cv128<UB_Z - j, HC>(y, f[0], f[1], f[2], f[3], dU);
        wg_commit();
        if (j + 2 < 18) {
          wg_wait<2>();
          pin<4>(fr[(j + 2) & 3]);
          load_frag(fr[(j + 2) & 3], pa + (j + 2) * 128);
          if (j == 1 && lane == 0) mbar_arrive(sb + BAR_FREE);
        }
      });
      wg_wait<0>();
      pin<64>(y);
      pin<16>(&fr[0][0]);
      STAMP_IF(bt == 0 && c == 1, 35);
#pragma unroll
      for (int b = 15; b >= 2; b--) { y[4 * b] += y[4 * b - 6]; y[4 * b + 1] += y[4 * b - 5]; }
      if (c > 0) mbar_wait(sb + BAR_XF, (c - 1) & 1);
      const uint32_t xa = sb + SM_XCH + r * 512 + lane * 16;
      if (p == 0) {
#pragma unroll
        for (int i = 0; i < 4; i++)
          sts128(xa + i * 1024, __float_as_uint(y[32 + 8 * i]), __float_as_uint(y[33 + 8 * i]), __float_as_uint(y[36 + 8 * i]), __float_as_uint(y[37 + 8 * i]));
      } else {
#pragma unroll
        for (int i = 0; i < 2; i++)
          sts128(xa + SM_XCH2 - SM_XCH + i * 1024, __float_as_uint(y[8 * i]), __float_as_uint(y[8 * i + 1]), __float_as_uint(y[8 * i + 4]), __float_as_uint(y[8 * i + 5]));
      }
      bar_sync<2, 128>();
      if (bt == 0 && c < 3) {
        mbar_expect(sb + BAR_UB + 8 * (c & 1), 2 * UB_C);
        tma4d(ub, &P.ut, sb + BAR_UB + 8 * (c & 1), 0, -(int)UB_Z, 0, ch0 + c + 2);
      }
      uint32_t* yd = g_yT + (ch0 + c) * 1024 + q * 16 + 8 * r + g + p * 512;
      if (p == 0) {
        const uint4 v0 = lds128(xa + SM_XCH2 - SM_XCH), v1 = lds128(xa + SM_XCH2 - SM_XCH + 1024);
#pragma unroll
        for (int i = 0; i < 4; i++) yd[i * 64] = pack_bf16(y[4 * i], y[4 * i + 1]);
        yd[256] = pack_bf16(y[16] + __uint_as_float(v0.x), y[17] + __uint_as_float(v0.y));
        yd[320] = pack_bf16(y[20] + __uint_as_float(v0.z), y[21] + __uint_as_float(v0.w));
        yd[384] = pack_bf16(y[24] + __uint_as_float(v1.x), y[25] + __uint_as_float(v1.y));
        yd[448] = pack_bf16(y[28] + __uint_as_float(v1.z), y[29] + __uint_as_float(v1.w));
      } else {
        uint4 v[4];
#pragma unroll
        for (int i = 0; i < 4; i++) v[i] = lds128(xa + i * 1024);
#pragma unroll
        for (int i = 0; i < 4; i++) {
          yd[i * 128] = pack_bf16(y[16 + 8 * i] + __uint_as_float(v[i].x), y[17 + 8 * i] + __uint_as_float(v[i].y));
          yd[i * 128 + 64] = pack_bf16(y[20 + 8 * i] + __uint_as_float(v[i].z), y[21 + 8 * i] + __uint_as_float(v[i].w));
        }
      }
      __syncwarp();
      if (lane == 0) mbar_arrive(sb + BAR_XF);
      STAMP_IF(bt == 0, 26 + c);
    }
    bar_sync<2, 128>();
    if (bt == 0) {
      signal(CNT_Y + grp);
      wait_count(CNT_Y + grp, (epoch + 1) * 32);
    }
    bar_sync<2, 128>();
    STAMP_IF(bt == 0, 31);
    {
      uint4 L[3][4];
#pragma unroll
      for (int bi = 0; bi < 3; bi++) {
        const int blk = wp + 4 * bi;
        if (blk < 10) {
          const int m = 2 * gi + blk / 5, c0 = 160 * grp + 32 * (blk % 5);
#pragma unroll
          for (int j = 0; j < 4; j++)
            L[bi][j] = __ldcg(reinterpret_cast<const uint4*>(g_yT + (c0 + 8 * (g >> 1) + 2 * j + (g & 1)) * 1024 + m * 16 + 4 * q));
        }
      }
#pragma unroll
      for (int bi = 0; bi < 3; bi++) {
        const int blk = wp + 4 * bi;
        if (blk < 10) {
          const int m = 2 * gi + blk / 5, c0 = 160 * grp + 32 * (blk % 5);
          transpose_store(L[bi], reinterpret_cast<uint4*>(P.outp + (size_t)(32 * m + 16 * (g & 1) + 4 * (g >> 1)) * 1280 + 640 + c0 + 8 * q), 160);
        }
      }
    }
    STAMP_IF(bt == 0, 32);
  } else {
    asm volatile("setmaxnreg.inc.sync.aligned.u32 168;");
    const int wg = tid >> 7;
    uint32_t qf[20], kf[20];
    float pk[40], pq[40];
    {
      float acc[120];
#pragma unroll
      for (int i = 0; i < 120; i++) acc[i] = 0.f;
      auto qkv_wait = [&](int it) { mbar_wait(sb + BAR_FULL + 8 * (it & 3), (it >> 2) & 1); };
      auto qkv_step = [&](int it) {
        const uint32_t d = sb + (it & 3) * STAGE;
        const uint32_t da = dlo(d + wg * 8192, 16), db1 = dlo(d + OFF_W128, 8192), db2 = dlo(d + OFF_W16, 2048);
        static_for<0, 4>([&](auto k) {
          mma_qkv192<k * 2, dhi(1024, 1), k * 128, dhi(1024, 1)>(acc, da, db1);
          mma_qkv48<k * 2, dhi(1024, 1), k * 32, dhi(256, 3)>(acc + 96, da, db2);
        });
        wg_commit();
      };
      auto release = [&](int it) {
        if (it < 8 && (tid & 127) == 0) mbar_arrive(it < 6 ? sb + BAR_EMPTY + 8 * (it & 3) : sb + BAR_S6 + 8 * (it - 6));
      };
#pragma unroll 1
      for (int it = 0; it < 10; it++) {
        qkv_wait(it);
        STAMP_IF(tid == 0 && it == 0, 0);
        wg_fence();
        qkv_step(it);
        if (it > 0) {
          wg_wait<1>();
          release(it - 1);
        }
      }
      wg_wait<0>();
      pin<120>(acc);
      if ((tid & 127) == 0) mbar_arrive(sb + BAR_MAIN);
      STAMP_IF(tid == 0, 1);
#pragma unroll
      for (int i = 0; i < 16; i++) {
        qf[i] = pack_bf16(acc[2 * i], acc[2 * i + 1]);
        kf[i] = pack_bf16(acc[32 + 2 * i], acc[33 + 2 * i]);
      }
#pragma unroll
      for (int i = 0; i < 4; i++) {
        qf[16 + i] = pack_bf16(acc[96 + 2 * i], acc[97 + 2 * i]);
        kf[16 + i] = pack_bf16(acc[104 + 2 * i], acc[105 + 2 * i]);
      }
      bar_sync<3, 320>();
      fence_async_smem();
      ROW_IDS
      const uint32_t va = sb + SM_V + row * 16 + q * 4;
#pragma unroll
      for (int b = 0; b < 10; b++) {
        const float* a = b < 8 ? acc + 64 + 4 * b : acc + 112 + 4 * (b - 8);
        sts32(va + (b + (b >= 5)) * 2048, pack_bf16(a[0], a[1]));
        sts32(va + (b + (b >= 5)) * 2048 + 128, pack_bf16(a[2], a[3]));
      }
      sts128(sb + SM_V + 10240 + wg * 12288 + (tid_ & 127) * 16, 0x3F803F80u, 0x3F803F80u, 0x3F803F80u, 0x3F803F80u);
      wg_fence();
      mma_phi80_z<0, dhi(1280, 0)>(pk, kf[0], kf[1], kf[2], kf[3], dlo(sb + SM_WPHI, 128));
      static_for<1, 5>([&](auto c) { mma_phi80<c * 16, dhi(1280, 0)>(pk, kf[4 * c], kf[4 * c + 1], kf[4 * c + 2], kf[4 * c + 3], dlo(sb + SM_WPHI, 128)); });
      wg_commit();
      mma_phi80_z<0, dhi(1280, 0)>(pq, qf[0], qf[1], qf[2], qf[3], dlo(sb + SM_WPHI, 128));
      static_for<1, 5>([&](auto c) { mma_phi80<c * 16, dhi(1280, 0)>(pq, qf[4 * c], qf[4 * c + 1], qf[4 * c + 2], qf[4 * c + 3], dlo(sb + SM_WPHI, 128)); });
      wg_commit();
    }
    wg_wait<1>();
    pin<40>(pk);
    pin<20>(kf);
    STAMP_IF(tid == 0, 2);
    {
      uint32_t ph[20];
      ROW_IDS
      const uint32_t ad = sb + SM_PHIK + q * 5 * PHIK_S + row * 16;
      dual_softmax<0>(pk, ph);
#pragma unroll
      for (int i = 0; i < 5; i++) sts128(ad + i * PHIK_S, ph[4 * i], ph[4 * i + 1], ph[4 * i + 2], ph[4 * i + 3]);
      dual_softmax<1>(pk, ph);
#pragma unroll
      for (int i = 0; i < 5; i++) sts128(ad + i * PHIK_S + 128, ph[4 * i], ph[4 * i + 1], ph[4 * i + 2], ph[4 * i + 3]);
    }
    wg_wait<0>();
    pin<40>(pq);
    if ((tid & 127) == 0) mbar_arrive(sb + BAR_PHI);
    fence_async_smem();
    STAMP_IF(tid == 0, 3);
    bar_sync<1, 256>();
    const unsigned epoch = lds32(sb + SM_EPOCH);
    {
      float kv[40];
      const uint32_t da = dlo(sb + SM_V + wg * 12288, 128), db = dlo(sb + SM_PHIK + wg * 10 * PHIK_S, 128);
      wg_fence();
      mma_kv80_z<0, dhi(2048, 0), 0, dhi(PHIK_S, 0)>(kv, da, db);
      static_for<1, 8>([&](auto k) { mma_kv80<k * 16, dhi(2048, 0), k * 16, dhi(PHIK_S, 0)>(kv, da, db); });
      wg_commit();
      wg_wait<0>();
      pin<40>(kv);
      bar_sync<1, 256>();
      LANE_IDS
      if (wp < 3) {
#pragma unroll
        for (int h = 0; h < 2; h++) {
          const int dr = 16 * wp + 8 * h + g;
          if (dr < 40) {
            const int hi = dr >= 20, dd = dr - 20 * hi;
            const uint32_t p = sb + SM_KVST + q * 720 + (8 * (dd >> 1) + 2 * (2 * wg + hi) + (dd & 1)) * 8;
#pragma unroll
            for (int i = 0; i < 5; i++)
              sts64(p + i * 2880, __float_as_uint(hi ? kv[20 + 4 * i + 2 * h] : kv[4 * i + 2 * h]), __float_as_uint(hi ? kv[21 + 4 * i + 2 * h] : kv[4 * i + 2 * h + 1]));
          } else if (g < 2) {
            const uint32_t p = sb + SM_KVST + q * 720 + (80 + 2 * (2 * wg + g)) * 8;
#pragma unroll
            for (int i = 0; i < 5; i++)
              sts64(p + i * 2880, __float_as_uint(g ? kv[22 + 4 * i] : kv[4 * i + 2]), __float_as_uint(g ? kv[23 + 4 * i] : kv[4 * i + 3]));
          }
        }
      }
      fence_async_smem();
      bar_arrive<4, 288>();
    }
    STAMP_IF(tid == 0, 4);
    uint32_t pa[20], pb[20];
    dual_softmax<0>(pq, pa);
    dual_softmax<1>(pq, pb);
    STAMP_IF(tid == 0, 5);
    {
      if (tid == 0) wait_count(CNT_KV + hg, (epoch + 1) * 16);
      bar_sync<1, 256>();
      STAMP_IF(tid == 0, 6);
      LANE_IDS
      const float2* src = reinterpret_cast<const float2*>(g_kv + (epoch & 1) * 28800 + hg * 3600) + tid_;
      float2 t[8];
#pragma unroll
      for (int i = 0; i < 8; i++)
        if (i < 7 || tid_ < 8) t[i] = __ldcg(src + 256 * i);
      int n = tid_ % 90;
#pragma unroll
      for (int i = 0; i < 8; i++) {
        if (i < 7 || tid_ < 8) {
          const int j = (n >> 1) & 3;
          const uint32_t w = pack_bf16(t[i].x, t[i].y);
          sts128(sb + SM_KVB + (tid_ + 256 * i) * 16, j == 0 ? w : 0u, j == 1 ? w : 0u, j == 2 ? w : 0u, j == 3 ? w : 0u);
        }
        n = n < 14 ? n + 76 : n - 14;
      }
      if (tid_ == 255) mbar_arrive(sb + BAR_KVB);
    }
    fence_async_smem();
    bar_sync<1, 256>();
    STAMP_IF(tid == 0, 7);
    {
      float o[44];
      wg_fence();
      mma_o88_z<0, dhi(128, 0)>(o, pa[0], pb[0], pa[1], pb[1], dlo(sb + SM_KVB, 1440));
      static_for<1, 10>([&](auto c) { mma_o88<c * 180, dhi(128, 0)>(o, pa[2 * c], pb[2 * c], pa[2 * c + 1], pb[2 * c + 1], dlo(sb + SM_KVB, 1440)); });
      wg_commit();
      wg_wait<0>();
      pin<44>(o);
      pin<20>(pa);
      pin<20>(pb);
      STAMP_IF(tid == 0, 8);
      ROW_IDS
      const float r0 = 1.0f / (o[40] + 1e-6f), r1 = 1.0f / (o[42] + 1e-6f);
      const uint32_t d0 = sb + SM_OST + row * 160 + q * 40;
#pragma unroll
      for (int i = 0; i < 5; i++) {
        sts64(d0 + 8 * i, pack_bf16(o[8 * i] * r0, o[8 * i + 1] * r0), pack_bf16(o[8 * i + 4] * r0, o[8 * i + 5] * r0));
        sts64(d0 + 8 * i + 1280, pack_bf16(o[8 * i + 2] * r1, o[8 * i + 3] * r1), pack_bf16(o[8 * i + 6] * r1, o[8 * i + 7] * r1));
      }
      fence_async_smem();
      bar_arrive<5, 288>();
    }
    STAMP_IF(tid == 0, 9);
    float acc[40];
#pragma unroll
    for (int i = 0; i < 40; i++) acc[i] = 0.f;
    mbar_wait(sb + BAR_WO, 0);
#pragma unroll 1
    for (int it = 0; it < 10; it++) {
      const int s = it < 5 ? it : it - 5;
      mbar_wait(sb + BAR_OFULL + 8 * s, it >= 5);
      STAMP_IF(tid == 0 && it == 0, 10);
      const uint32_t da = dlo(sb + (s < 4 ? s * 16384 : SM_O4) + wg * 8192, 16), db = dlo(sb + SM_WO + it * 10240, 2048);
      wg_fence();
      static_for<0, 4>([&](auto k) { mma_out80<k * 2, dhi(1024, 1), k * 32, dhi(256, 3)>(acc, da, db); });
      wg_commit();
      if (it > 0) {
        wg_wait<1>();
        if (it < 6 && (tid & 127) == 0) mbar_arrive(sb + BAR_OEMPTY + 8 * (it - 1));
      }
    }
    wg_wait<0>();
    pin<40>(acc);
    STAMP_IF(tid == 0, 11);
    bar_sync<1, 256>();
    {
      LANE_IDS
      const uint32_t st = sb + wg * 10240;
      const uint32_t ad = st + (wp * 16 + (lane & 15)) * 160 + (lane >> 4) * 16;
#pragma unroll
      for (int i = 0; i < 5; i++) {
        asm volatile("stmatrix.sync.aligned.m8n8.x4.shared.b16 [%0], {%1,%2,%3,%4};" ::"r"(ad + i * 32),
                     "r"(pack_bf16(acc[8 * i], acc[8 * i + 1])), "r"(pack_bf16(acc[8 * i + 2], acc[8 * i + 3])),
                     "r"(pack_bf16(acc[8 * i + 4], acc[8 * i + 5])), "r"(pack_bf16(acc[8 * i + 6], acc[8 * i + 7])) : "memory");
      }
      fence_async_smem();
      if (wg == 0) bar_sync<7, 128>(); else bar_sync<8, 128>();
      if ((tid & 127) == 0) {
        tma2d_store(&P.out, st, hg * 80, rb * 128 + wg * 64);
        asm volatile("cp.async.bulk.commit_group;" ::: "memory");
        asm volatile("cp.async.bulk.wait_group.read 0;" ::: "memory");
      }
    }
    STAMP_IF(tid == 0, 12);
  }
}

typedef CUresult (*EncodeFn)(CUtensorMap*, CUtensorMapDataType, cuuint32_t, void*, const cuuint64_t*, const cuuint64_t*,
                             const cuuint32_t*, const cuuint32_t*, CUtensorMapInterleave, CUtensorMapSwizzle,
                             CUtensorMapL2promotion, CUtensorMapFloatOOBfill);

void encode(EncodeFn fn, CUtensorMap* m, const void* p, int rank, const cuuint64_t* dims, const cuuint64_t* strides,
            const cuuint32_t* box, CUtensorMapSwizzle sw) {
  const cuuint32_t es[5] = {1, 1, 1, 1, 1};
  fn(m, CU_TENSOR_MAP_DATA_TYPE_BFLOAT16, rank, const_cast<void*>(p), dims, strides, box, es, CU_TENSOR_MAP_INTERLEAVE_NONE, sw,
     CU_TENSOR_MAP_L2_PROMOTION_NONE, CU_TENSOR_MAP_FLOAT_OOB_FILL_NONE);
}

int build_tile_map(uint8_t* map) {
  int dev = 0, nsm = 0;
  cudaGetDevice(&dev);
  cudaDeviceGetAttribute(&nsm, cudaDevAttrMultiProcessorCount, dev);
  if (nsm > 192) nsm = 192;
  for (int i = 0; i < 192; i++) map[i] = (uint8_t)(i < NCTA ? i : 255);
  cudaFuncSetAttribute(fused_kernel, cudaFuncAttributeNonPortableClusterSizeAllowed, 1);
  int f[17] = {0};
  for (int c = 2; c <= 16; c++) {
    cudaLaunchConfig_t cfg = {};
    cfg.gridDim = dim3(c);
    cfg.blockDim = dim3(512);
    cfg.dynamicSmemBytes = SMEM_BYTES;
    cudaLaunchAttribute at[1];
    at[0].id = cudaLaunchAttributeClusterDimension;
    at[0].val.clusterDim.x = c; at[0].val.clusterDim.y = 1; at[0].val.clusterDim.z = 1;
    cfg.attrs = at;
    cfg.numAttrs = 1;
    if (cudaOccupancyMaxActiveClusters(&f[c], fused_kernel, &cfg) != cudaSuccess) { cudaGetLastError(); return nsm; }
  }
  int n[10];
  n[5] = f[10]; n[6] = f[12]; n[7] = f[14]; n[8] = f[16];
  n[9] = f[9] - n[5];
  n[4] = f[8] - n[8];
  n[3] = f[6] - n[6] - n[9];
  n[2] = f[4] - n[4] - n[6] - n[8];
  n[1] = n[2];
  int ntpc = 0;
  for (int r = 1; r <= 9; r++) ntpc += n[r];
  if (2 * f[2] != nsm || ntpc > f[2] || n[1] > 8 || n[9] < 0 || nsm < NCTA) return nsm;
  for (int r = 1; r < 9; r++) if (n[r] < n[r + 1]) return nsm;
  int pair_of[96];
  bool taken[64] = {false};
  int t = 0;
  for (int r = 1; r <= 9; r++)
    for (int p = n[1] - n[r]; p < n[1]; p++, t++) {
      pair_of[t] = r <= 8 ? p * 8 + r - 1 : -1;
      if (r <= 8) taken[pair_of[t]] = true;
    }
  for (; t < f[2]; t++) pair_of[t] = -1;
  for (int pr = 0; pr < 64; pr++)
    for (int u = f[2] - 1; u >= 0 && !taken[pr]; u--)
      if (pair_of[u] < 0) { pair_of[u] = pr; taken[pr] = true; }
  for (int u = 0; u < f[2]; u++)
    for (int e = 0; e < 2; e++) {
      const int pr = pair_of[u], blk = pr >> 3, i = pr & 7;
      map[2 * u + e] = pr < 0 ? 255 : (uint8_t)(((blk >> 1) * 4 + (i & 1) * 2 + e) * 8 + (blk & 1) * 4 + (i >> 1));
    }
  return nsm;
}

}

extern "C" void kernel_launch(void* const* d_in, const int* in_sizes, int n_in, void* d_out, int out_size) {
  (void)in_sizes; (void)n_in; (void)out_size;
  void* fnp = nullptr;
  cudaDriverEntryPointQueryResult qr;
  cudaGetDriverEntryPoint("cuTensorMapEncodeTiled", &fnp, cudaEnableDefault, &qr);
  EncodeFn fn = (EncodeFn)fnp;
  void *uT = nullptr, *O = nullptr;
  cudaGetSymbolAddress(&uT, g_uT);
  cudaGetSymbolAddress(&O, g_O);

  Params P;
  { const cuuint64_t d[2] = {640, 2048}, s[1] = {1280}; const cuuint32_t b[2] = {64, 128};
    encode(fn, &P.x, d_in[0], 2, d, s, b, CU_TENSOR_MAP_SWIZZLE_128B);
    encode(fn, &P.o, O, 2, d, s, b, CU_TENSOR_MAP_SWIZZLE_128B);
    const cuuint32_t b2[2] = {80, 128};
    encode(fn, &P.ost, O, 2, d, s, b2, CU_TENSOR_MAP_SWIZZLE_NONE); }
  { const cuuint64_t d[3] = {640, 640, 3}, s[2] = {3840, 1280}; const cuuint32_t b1[3] = {64, 64, 3}, b2[3] = {16, 64, 3};
    encode(fn, &P.w128, d_in[1], 3, d, s, b1, CU_TENSOR_MAP_SWIZZLE_128B);
    encode(fn, &P.w16, d_in[1], 3, d, s, b2, CU_TENSOR_MAP_SWIZZLE_32B); }
  { const cuuint64_t d[3] = {16, 640, 40}, s[2] = {1280, 32}; const cuuint32_t b[3] = {16, 64, 5};
    encode(fn, &P.wo, d_in[3], 3, d, s, b, CU_TENSOR_MAP_SWIZZLE_32B); }
  { const cuuint64_t d[4] = {8, 128, 2, 640}, s[3] = {32, 16, 4096}; const cuuint32_t b[4] = {8, 148, 2, 1};
    encode(fn, &P.ut, uT, 4, d, s, b, CU_TENSOR_MAP_SWIZZLE_NONE); }
  { const cuuint64_t d[2] = {1280, 2048}, s[1] = {2560}; const cuuint32_t b[2] = {80, 64};
    encode(fn, &P.out, d_out, 2, d, s, b, CU_TENSOR_MAP_SWIZZLE_NONE); }
  P.wphi = (const uint32_t*)d_in[2];
  P.u = (const __nv_bfloat16*)d_in[4];
  for (int i = 0; i < 6; i++) P.ssm[i] = (const uint16_t*)d_in[5 + i];
  P.logdt = (const uint16_t*)d_in[11]; P.dskip = (const uint16_t*)d_in[12];
  P.outp = (__nv_bfloat16*)d_out;

  cudaFuncSetAttribute(fused_kernel, cudaFuncAttributeMaxDynamicSharedMemorySize, SMEM_BYTES);
  static int nsm = 0;
  static uint8_t tile_map[192];
  if (nsm == 0) nsm = build_tile_map(tile_map);
  for (int i = 0; i < 192; i++) P.tile_of_sm[i] = tile_map[i];
  P.nsm = nsm;
  for (int i = 0; i < 36; i++) P.bar_count[i] = (uint8_t)(((BAR_COUNT2 >> (i & 31)) & 1) + 1);
  P.bar_count[(BAR_PHI - SM_MISC) / 8] = 2;
  P.bar_count[(BAR_K0 - SM_MISC) / 8] = P.bar_count[(BAR_PRF - SM_MISC) / 8] = P.bar_count[(BAR_KGD - SM_MISC) / 8] = 128;
  P.bar_count[(BAR_RDY - SM_MISC) / 8] = 96;
  P.bar_count[(BAR_XF - SM_MISC) / 8] = P.bar_count[(BAR_FREE - SM_MISC) / 8] = 4;
  fused_kernel<<<nsm, 512, SMEM_BYTES, cudaStreamPerThread>>>(P);
}
```

```cpp
#include <cuda_runtime.h>
#include <cuda.h>
#include <cuda_bf16.h>
#include <cuda_fp16.h>
#include <stdint.h>

#define STORE2_AT BAR_S7

namespace {

constexpr int NCTA = 128;
constexpr int SPIN_LIMIT = 1 << 22;

constexpr uint32_t STAGE    = 47104;
constexpr uint32_t OFF_W128 = 16384;
constexpr uint32_t OFF_W16  = 40960;
constexpr uint32_t SM_PHIK  = 0;
constexpr uint32_t PHIK_S   = 2080;
constexpr uint32_t SM_V     = 41600;
constexpr uint32_t SM_KVST  = SM_V;
constexpr uint32_t SM_KVB   = 0;
constexpr uint32_t SM_OST   = 28800;
constexpr uint32_t SM_WO    = 81920;
constexpr uint32_t SM_WPHI  = 2 * STAGE + 32768;
constexpr uint32_t SM_B     = 4 * STAGE;
constexpr uint32_t SM_KZ    = SM_B;
constexpr uint32_t SM_KG    = SM_B + 6528;
constexpr uint32_t SM_KG2   = 2 * STAGE;
constexpr uint32_t SM_PT0   = 66176;
constexpr uint32_t SM_H     = SM_PT0 + 4864;
constexpr uint32_t SM_W     = SM_H + 4352;
constexpr uint32_t SM_XCH2  = SM_W + 4096;
constexpr uint32_t SM_UB4   = 49408;
constexpr uint32_t SM_PT4   = SM_UB4 + 4864;
constexpr uint32_t SM_H4    = SM_PT4 + 4864;
constexpr uint32_t SM_O4    = SM_B + 7168;
constexpr uint32_t SM_PT1   = SM_B + 23552;
constexpr uint32_t SM_UB1   = SM_B + 28416;
constexpr uint32_t SM_XCH   = SM_B + 33280;
constexpr uint32_t SM_UB0   = SM_B + 38400;
constexpr int UB_Z = 24;
constexpr uint32_t SM_WP    = SM_B + 35200;
constexpr uint32_t SM_MISC  = SM_B + 43456;
constexpr uint32_t BAR_FULL   = SM_MISC;
constexpr uint32_t BAR_EMPTY  = SM_MISC + 32;
constexpr uint32_t BAR_WO     = SM_MISC + 64;
constexpr uint32_t BAR_OFULL  = SM_MISC + 72;
constexpr uint32_t BAR_OEMPTY = SM_MISC + 112;
constexpr uint32_t BAR_UB     = SM_MISC + 152;
constexpr uint32_t BAR_EPOCH  = SM_MISC + 168;
constexpr uint32_t BAR_MAIN   = SM_MISC + 176;
constexpr uint32_t BAR_S6     = SM_MISC + 184;
constexpr uint32_t BAR_S7     = SM_MISC + 192;
constexpr uint32_t BAR_COUNT2 = 0xF0u | (0x1Fu << 14) | (7u << 22);
constexpr uint32_t SM_EPOCH = SM_MISC + 296;
constexpr uint32_t BAR_PHI    = SM_MISC + 224;
constexpr uint32_t BAR_KGD    = SM_MISC + 232;
constexpr uint32_t BAR_RDY    = SM_MISC + 240;
constexpr uint32_t BAR_XF     = SM_MISC + 256;
constexpr uint32_t BAR_PRM    = SM_MISC + 264;
constexpr uint32_t BAR_PRF    = SM_MISC + 216;
constexpr uint32_t BAR_K0     = SM_MISC + 208;
constexpr uint32_t BAR_FREE   = SM_MISC + 248;
constexpr uint32_t SM_CMAX  = SM_KZ + 4 * 1296;
constexpr uint32_t BAR_CV     = SM_MISC + 280;
constexpr uint32_t BAR_AXF    = SM_MISC + 288;
constexpr uint32_t BAR_RD4    = SM_MISC + 304;
constexpr uint32_t BAR_CVA    = SM_MISC + 312;
constexpr uint32_t BAR_RD3    = SM_MISC + 320;
constexpr uint32_t BAR_KVB    = SM_MISC + 272;
constexpr uint32_t BAR_WP     = SM_MISC + 200;
constexpr uint32_t SM_STAMP = SM_MISC + 328;
constexpr uint32_t SMEM_BYTES = SM_MISC + 576;

__device__ __align__(1024) __nv_bfloat16 g_uT[640 * 2048];
__device__ __align__(1024) uint32_t g_yT[640 * 1024];
__device__ __align__(1024) __nv_bfloat16 g_O[2048 * 640];
__device__ __align__(1024) float g_kv[2 * 8 * 3600];
__device__ __align__(1024) unsigned g_cnt[40 * 32];
constexpr int CNT_START = 0, CNT_KV = 1, CNT_O = 9, CNT_T1 = 25, CNT_Y = 29;

#define STAMP(i)
#define STAMP_FLUSH(lo, hi)
#define STAMP_IF(c, i)

struct Params {
  uint8_t tile_of_sm[192];
  unsigned nsm;
  uint8_t bar_count[36];
  CUtensorMap x, w128, w16, wo, o, ost, out;
  const uint32_t* wphi;
  const __nv_bfloat16* u;
  const uint16_t* ssm[6];
  const uint16_t *logdt, *dskip;
  __nv_bfloat16* outp;
};

__device__ __forceinline__ void mbar_init(uint32_t b, int c) { asm volatile("mbarrier.init.shared::cta.b64 [%0], %1;" ::"r"(b), "r"(c) : "memory"); }
__device__ __forceinline__ void mbar_expect(uint32_t b, int bytes) { asm volatile("mbarrier.arrive.expect_tx.shared::cta.b64 _, [%0], %1;" ::"r"(b), "r"(bytes) : "memory"); }
__device__ __forceinline__ void mbar_arrive(uint32_t b) { asm volatile("mbarrier.arrive.shared::cta.b64 _, [%0];" ::"r"(b) : "memory"); }
__device__ __forceinline__ void mbar_wait(uint32_t b, int parity) {
  asm volatile("{\n.reg .pred p;\n.reg .u32 n;\nmov.u32 n, %2;\n"
               "WAIT:\nmbarrier.try_wait.parity.shared::cta.b64 p, [%0], %1;\n@p bra DONE;\n"
               "sub.u32 n, n, 1;\nsetp.ne.u32 p, n, 0;\n@p bra WAIT;\nDONE:\n}" ::"r"(b), "r"(parity), "n"(SPIN_LIMIT) : "memory");
}
__device__ __forceinline__ bool mbar_test(uint32_t b, int parity) {
  uint32_t ok;
  asm volatile("{\n.reg .pred p;\nmbarrier.test_wait.parity.shared::cta.b64 p, [%1], %2;\nselp.u32 %0, 1, 0, p;\n}" : "=r"(ok) : "r"(b), "r"(parity) : "memory");
  return ok;
}
__device__ __forceinline__ void tma2d(uint32_t dst, const CUtensorMap* m, uint32_t bar, int c0, int c1) {
  asm volatile("cp.async.bulk.tensor.2d.shared::cluster.global.mbarrier::complete_tx::bytes [%0], [%1, {%3,%4}], [%2];" ::"r"(dst), "l"(m), "r"(bar), "r"(c0), "r"(c1) : "memory");
}
__device__ __forceinline__ void tma3d(uint32_t dst, const CUtensorMap* m, uint32_t bar, int c0, int c1, int c2) {
  asm volatile("cp.async.bulk.tensor.3d.shared::cluster.global.mbarrier::complete_tx::bytes [%0], [%1, {%3,%4,%5}], [%2];" ::"r"(dst), "l"(m), "r"(bar), "r"(c0), "r"(c1), "r"(c2) : "memory");
}
__device__ __forceinline__ void bulk_load(uint32_t dst, const void* src, int bytes, uint32_t bar) {
  asm volatile("cp.async.bulk.shared::cluster.global.mbarrier::complete_tx::bytes [%0], [%1], %2, [%3];" ::"r"(dst), "l"(src), "r"(bytes), "r"(bar) : "memory");
}
__device__ __forceinline__ void tma2d_store(const CUtensorMap* m, uint32_t src, int c0, int c1) {
  asm volatile("cp.async.bulk.tensor.2d.global.shared::cta.bulk_group [%0, {%2,%3}], [%1];" ::"l"(m), "r"(src), "r"(c0), "r"(c1) : "memory");
}
__device__ __forceinline__ void fence_async_smem() { asm volatile("fence.proxy.async.shared::cta;" ::: "memory"); }
__device__ __forceinline__ void fence_async_global() { asm volatile("fence.proxy.async.global;" ::: "memory"); }
__device__ __forceinline__ void bulk_commit_wait() {
  asm volatile("cp.async.bulk.commit_group;" ::: "memory");
  asm volatile("cp.async.bulk.wait_group 0;" ::: "memory");
}
template <int ID, int N> __device__ __forceinline__ void bar_sync() { asm volatile("bar.sync %0, %1;" ::"n"(ID), "n"(N) : "memory"); }
template <int ID, int N> __device__ __forceinline__ void bar_arrive() { asm volatile("bar.arrive %0, %1;" ::"n"(ID), "n"(N) : "memory"); }
__device__ __forceinline__ void wg_fence() { asm volatile("wgmma.fence.sync.aligned;" ::: "memory"); }
__device__ __forceinline__ void wg_commit() { asm volatile("wgmma.commit_group.sync.aligned;" ::: "memory"); }
template <int N> __device__ __forceinline__ void wg_wait() { asm volatile("wgmma.wait_group.sync.aligned %0;" ::"n"(N) : "memory"); }
template <int N> __device__ __forceinline__ void pin(float* d) {
#pragma unroll
  for (int i = 0; i < N; i++) asm volatile("" : "+f"(d[i])::"memory");
}
template <int N> __device__ __forceinline__ void pin(uint32_t* d) {
#pragma unroll
  for (int i = 0; i < N; i++) asm volatile("" : "+r"(d[i])::"memory");
}
__device__ __forceinline__ uint32_t dlo(uint32_t addr, uint32_t lbo) { return ((addr & 0x3FFFF) >> 4) | ((lbo >> 4) << 16); }
__host__ __device__ constexpr uint32_t dhi(uint32_t sbo, uint32_t sw) { return (sbo >> 4) | (sw << 30); }
template <int V> struct IC { __host__ __device__ constexpr operator int() const { return V; } };
template <int I, int N, class F> __device__ __forceinline__ void static_for(F&& f) {
  if constexpr (I < N) { f(IC<I>{}); static_for<I + 1, N>(f); }
}
__device__ __forceinline__ uint32_t pack_bf16(float lo, float hi) {
  uint32_t r;
  asm("cvt.rn.bf16x2.f32 %0, %1, %2;" : "=r"(r) : "f"(hi), "f"(lo));
  return r;
}
__device__ __forceinline__ uint32_t pack_f16(float lo, float hi) {
  uint32_t r;
  asm("cvt.rn.f16x2.f32 %0, %1, %2;" : "=r"(r) : "f"(hi), "f"(lo));
  return r;
}
__device__ __forceinline__ float ex2(float x) { float r; asm("ex2.approx.ftz.f32 %0, %1;" : "=f"(r) : "f"(x)); return r; }
__device__ __forceinline__ float rcp(float x) { float r; asm("rcp.approx.ftz.f32 %0, %1;" : "=f"(r) : "f"(x)); return r; }
__device__ __forceinline__ float bf2f(uint32_t h) { return __uint_as_float(h << 16); }
__device__ __forceinline__ void sts32(uint32_t a, uint32_t v) { asm volatile("st.shared.u32 [%0], %1;" ::"r"(a), "r"(v) : "memory"); }
__device__ __forceinline__ void sts16(uint32_t a, uint32_t v) { asm volatile("st.shared.u16 [%0], %1;" ::"r"(a), "h"((uint16_t)v) : "memory"); }
__device__ __forceinline__ void sts64(uint32_t a, uint32_t x, uint32_t y) { asm volatile("st.shared.v2.u32 [%0], {%1,%2};" ::"r"(a), "r"(x), "r"(y) : "memory"); }
__device__ __forceinline__ void sts128(uint32_t a, uint32_t x, uint32_t y, uint32_t z, uint32_t w) { asm volatile("st.shared.v4.u32 [%0], {%1,%2,%3,%4};" ::"r"(a), "r"(x), "r"(y), "r"(z), "r"(w) : "memory"); }
__device__ __forceinline__ uint32_t lds32(uint32_t a) { uint32_t v; asm volatile("ld.shared.u32 %0, [%1];" : "=r"(v) : "r"(a) : "memory"); return v; }
__device__ __forceinline__ uint32_t lds16(uint32_t a) { uint16_t v; asm volatile("ld.shared.u16 %0, [%1];" : "=h"(v) : "r"(a) : "memory"); return v; }
__device__ __forceinline__ uint2 lds64(uint32_t a) { uint2 v; asm volatile("ld.shared.v2.u32 {%0,%1}, [%2];" : "=r"(v.x), "=r"(v.y) : "r"(a) : "memory"); return v; }
__device__ __forceinline__ uint4 lds128(uint32_t a) { uint4 v; asm volatile("ld.shared.v4.u32 {%0,%1,%2,%3}, [%4];" : "=r"(v.x), "=r"(v.y), "=r"(v.z), "=r"(v.w) : "r"(a) : "memory"); return v; }
__device__ __forceinline__ uint32_t movm(uint32_t a) { uint32_t d; asm volatile("movmatrix.sync.aligned.m8n8.trans.b16 %0, %1;" : "=r"(d) : "r"(a)); return d; }
__device__ __forceinline__ void signal(int c) {
  asm volatile("red.release.gpu.global.add.u32 [%0], 1;" ::"l"(&g_cnt[c * 32]) : "memory");
}
__device__ __forceinline__ void wait_count(int c, unsigned target) {
  asm volatile("{\n.reg .pred p;\n.reg .u32 n, v;\nmov.u32 n, %2;\n"
               "WAIT:\nld.relaxed.gpu.global.u32 v, [%0];\nsub.u32 v, v, %1;\nsetp.ge.s32 p, v, 0;\n@p bra DONE;\n"
               "sub.u32 n, n, 1;\nsetp.ne.u32 p, n, 0;\n@p bra WAIT;\nDONE:\nfence.acquire.gpu;\n}" ::"l"(&g_cnt[c * 32]), "r"(target), "n"(SPIN_LIMIT) : "memory");
}

template <int OA, uint32_t HA, int OB, uint32_t HB> __device__ __forceinline__ void mma_qkv192(float* d, uint32_t a, uint32_t b) {
  asm volatile("{\n.reg .pred p;\nsetp.ne.b32 p, 1, 0;\n.reg .b32 ta, tb;\n.reg .b64 da, db;\nadd.u32 ta, %96, %98;\nmov.b64 da, {ta, %99};\nadd.u32 tb, %97, %100;\nmov.b64 db, {tb, %101};\n"
    "wgmma.mma_async.sync.aligned.m64n192k16.f32.bf16.bf16 {%0,%1,%2,%3,%4,%5,%6,%7,%8,%9,%10,%11,%12,%13,%14,%15,%16,%17,%18,%19,%20,%21,%22,%23,%24,%25,%26,%27,%28,%29,%30,%31,%32,%33,%34,%35,%36,%37,%38,%39,%40,%41,%42,%43,%44,%45,%46,%47,%48,%49,%50,%51,%52,%53,%54,%55,%56,%57,%58,%59,%60,%61,%62,%63,%64,%65,%66,%67,%68,%69,%70,%71,%72,%73,%74,%75,%76,%77,%78,%79,%80,%81,%82,%83,%84,%85,%86,%87,%88,%89,%90,%91,%92,%93,%94,%95}, da, db, p,1,1,0,1;\n}\n"
    : "+f"(d[0]),"+f"(d[1]),"+f"(d[2]),"+f"(d[3]),"+f"(d[4]),"+f"(d[5]),"+f"(d[6]),"+f"(d[7]),"+f"(d[8]),"+f"(d[9]),"+f"(d[10]),"+f"(d[11]),"+f"(d[12]),"+f"(d[13]),"+f"(d[14]),"+f"(d[15]),"+f"(d[16]),"+f"(d[17]),"+f"(d[18]),"+f"(d[19]),"+f"(d[20]),"+f"(d[21]),"+f"(d[22]),"+f"(d[23]),"+f"(d[24]),"+f"(d[25]),"+f"(d[26]),"+f"(d[27]),"+f"(d[28]),"+f"(d[29]),"+f"(d[30]),"+f"(d[31]),"+f"(d[32]),"+f"(d[33]),"+f"(d[34]),"+f"(d[35]),"+f"(d[36]),"+f"(d[37]),"+f"(d[38]),"+f"(d[39]),"+f"(d[40]),"+f"(d[41]),"+f"(d[42]),"+f"(d[43]),"+f"(d[44]),"+f"(d[45]),"+f"(d[46]),"+f"(d[47]),"+f"(d[48]),"+f"(d[49]),"+f"(d[50]),"+f"(d[51]),"+f"(d[52]),"+f"(d[53]),"+f"(d[54]),"+f"(d[55]),"+f"(d[56]),"+f"(d[57]),"+f"(d[58]),"+f"(d[59]),"+f"(d[60]),"+f"(d[61]),"+f"(d[62]),"+f"(d[63]),"+f"(d[64]),"+f"(d[65]),"+f"(d[66]),"+f"(d[67]),"+f"(d[68]),"+f"(d[69]),"+f"(d[70]),"+f"(d[71]),"+f"(d[72]),"+f"(d[73]),"+f"(d[74]),"+f"(d[75]),"+f"(d[76]),"+f"(d[77]),"+f"(d[78]),"+f"(d[79]),"+f"(d[80]),"+f"(d[81]),"+f"(d[82]),"+f"(d[83]),"+f"(d[84]),"+f"(d[85]),"+f"(d[86]),"+f"(d[87]),"+f"(d[88]),"+f"(d[89]),"+f"(d[90]),"+f"(d[91]),"+f"(d[92]),"+f"(d[93]),"+f"(d[94]),"+f"(d[95])
    : "r"(a),"r"(b),"n"(OA),"n"(HA),"n"(OB),"n"(HB));
}
template <int OA, uint32_t HA, int OB, uint32_t HB> __device__ __forceinline__ void mma_qkv48(float* d, uint32_t a, uint32_t b) {
  asm volatile("{\n.reg .pred p;\nsetp.ne.b32 p, 1, 0;\n.reg .b32 ta, tb;\n.reg .b64 da, db;\nadd.u32 ta, %24, %26;\nmov.b64 da, {ta, %27};\nadd.u32 tb, %25, %28;\nmov.b64 db, {tb, %29};\n"
    "wgmma.mma_async.sync.aligned.m64n48k16.f32.bf16.bf16 {%0,%1,%2,%3,%4,%5,%6,%7,%8,%9,%10,%11,%12,%13,%14,%15,%16,%17,%18,%19,%20,%21,%22,%23}, da, db, p,1,1,0,1;\n}\n"
    : "+f"(d[0]),"+f"(d[1]),"+f"(d[2]),"+f"(d[3]),"+f"(d[4]),"+f"(d[5]),"+f"(d[6]),"+f"(d[7]),"+f"(d[8]),"+f"(d[9]),"+f"(d[10]),"+f"(d[11]),"+f"(d[12]),"+f"(d[13]),"+f"(d[14]),"+f"(d[15]),"+f"(d[16]),"+f"(d[17]),"+f"(d[18]),"+f"(d[19]),"+f"(d[20]),"+f"(d[21]),"+f"(d[22]),"+f"(d[23])
    : "r"(a),"r"(b),"n"(OA),"n"(HA),"n"(OB),"n"(HB));
}
template <int OB, uint32_t HB> __device__ __forceinline__ void mma_phi80(float* d, uint32_t a0, uint32_t a1, uint32_t a2, uint32_t a3, uint32_t b) {
  asm volatile("{\n.reg .pred p;\nsetp.ne.b32 p, 1, 0;\n.reg .b32 tb;\n.reg .b64 db;\nadd.u32 tb, %44, %45;\nmov.b64 db, {tb, %46};\n"
    "wgmma.mma_async.sync.aligned.m64n80k16.f32.bf16.bf16 {%0,%1,%2,%3,%4,%5,%6,%7,%8,%9,%10,%11,%12,%13,%14,%15,%16,%17,%18,%19,%20,%21,%22,%23,%24,%25,%26,%27,%28,%29,%30,%31,%32,%33,%34,%35,%36,%37,%38,%39}, {%40,%41,%42,%43}, db, p,1,1,1;\n}\n"
    : "+f"(d[0]),"+f"(d[1]),"+f"(d[2]),"+f"(d[3]),"+f"(d[4]),"+f"(d[5]),"+f"(d[6]),"+f"(d[7]),"+f"(d[8]),"+f"(d[9]),"+f"(d[10]),"+f"(d[11]),"+f"(d[12]),"+f"(d[13]),"+f"(d[14]),"+f"(d[15]),"+f"(d[16]),"+f"(d[17]),"+f"(d[18]),"+f"(d[19]),"+f"(d[20]),"+f"(d[21]),"+f"(d[22]),"+f"(d[23]),"+f"(d[24]),"+f"(d[25]),"+f"(d[26]),"+f"(d[27]),"+f"(d[28]),"+f"(d[29]),"+f"(d[30]),"+f"(d[31]),"+f"(d[32]),"+f"(d[33]),"+f"(d[34]),"+f"(d[35]),"+f"(d[36]),"+f"(d[37]),"+f"(d[38]),"+f"(d[39])
    : "r"(a0),"r"(a1),"r"(a2),"r"(a3),"r"(b),"n"(OB),"n"(HB));
}
template <int OB, uint32_t HB> __device__ __forceinline__ void mma_phi80_z(float* d, uint32_t a0, uint32_t a1, uint32_t a2, uint32_t a3, uint32_t b) {
  asm volatile("{\n.reg .pred p;\nsetp.ne.b32 p, 0, 0;\n.reg .b32 tb;\n.reg .b64 db;\nadd.u32 tb, %44, %45;\nmov.b64 db, {tb, %46};\n"
    "wgmma.mma_async.sync.aligned.m64n80k16.f32.bf16.bf16 {%0,%1,%2,%3,%4,%5,%6,%7,%8,%9,%10,%11,%12,%13,%14,%15,%16,%17,%18,%19,%20,%21,%22,%23,%24,%25,%26,%27,%28,%29,%30,%31,%32,%33,%34,%35,%36,%37,%38,%39}, {%40,%41,%42,%43}, db, p,1,1,1;\n}\n"
    : "=f"(d[0]),"=f"(d[1]),"=f"(d[2]),"=f"(d[3]),"=f"(d[4]),"=f"(d[5]),"=f"(d[6]),"=f"(d[7]),"=f"(d[8]),"=f"(d[9]),"=f"(d[10]),"=f"(d[11]),"=f"(d[12]),"=f"(d[13]),"=f"(d[14]),"=f"(d[15]),"=f"(d[16]),"=f"(d[17]),"=f"(d[18]),"=f"(d[19]),"=f"(d[20]),"=f"(d[21]),"=f"(d[22]),"=f"(d[23]),"=f"(d[24]),"=f"(d[25]),"=f"(d[26]),"=f"(d[27]),"=f"(d[28]),"=f"(d[29]),"=f"(d[30]),"=f"(d[31]),"=f"(d[32]),"=f"(d[33]),"=f"(d[34]),"=f"(d[35]),"=f"(d[36]),"=f"(d[37]),"=f"(d[38]),"=f"(d[39])
    : "r"(a0),"r"(a1),"r"(a2),"r"(a3),"r"(b),"n"(OB),"n"(HB));
}
template <int OA, uint32_t HA, int OB, uint32_t HB> __device__ __forceinline__ void mma_kv80(float* d, uint32_t a, uint32_t b) {
  asm volatile("{\n.reg .pred p;\nsetp.ne.b32 p, 1, 0;\n.reg .b32 ta, tb;\n.reg .b64 da, db;\nadd.u32 ta, %40, %42;\nmov.b64 da, {ta, %43};\nadd.u32 tb, %41, %44;\nmov.b64 db, {tb, %45};\n"
    "wgmma.mma_async.sync.aligned.m64n80k16.f32.bf16.bf16 {%0,%1,%2,%3,%4,%5,%6,%7,%8,%9,%10,%11,%12,%13,%14,%15,%16,%17,%18,%19,%20,%21,%22,%23,%24,%25,%26,%27,%28,%29,%30,%31,%32,%33,%34,%35,%36,%37,%38,%39}, da, db, p,1,1,1,1;\n}\n"
    : "+f"(d[0]),"+f"(d[1]),"+f"(d[2]),"+f"(d[3]),"+f"(d[4]),"+f"(d[5]),"+f"(d[6]),"+f"(d[7]),"+f"(d[8]),"+f"(d[9]),"+f"(d[10]),"+f"(d[11]),"+f"(d[12]),"+f"(d[13]),"+f"(d[14]),"+f"(d[15]),"+f"(d[16]),"+f"(d[17]),"+f"(d[18]),"+f"(d[19]),"+f"(d[20]),"+f"(d[21]),"+f"(d[22]),"+f"(d[23]),"+f"(d[24]),"+f"(d[25]),"+f"(d[26]),"+f"(d[27]),"+f"(d[28]),"+f"(d[29]),"+f"(d[30]),"+f"(d[31]),"+f"(d[32]),"+f"(d[33]),"+f"(d[34]),"+f"(d[35]),"+f"(d[36]),"+f"(d[37]),"+f"(d[38]),"+f"(d[39])
    : "r"(a),"r"(b),"n"(OA),"n"(HA),"n"(OB),"n"(HB));
}
template <int OA, uint32_t HA, int OB, uint32_t HB> __device__ __forceinline__ void mma_kv80_z(float* d, uint32_t a, uint32_t b) {
  asm volatile("{\n.reg .pred p;\nsetp.ne.b32 p, 0, 0;\n.reg .b32 ta, tb;\n.reg .b64 da, db;\nadd.u32 ta, %40, %42;\nmov.b64 da, {ta, %43};\nadd.u32 tb, %41, %44;\nmov.b64 db, {tb, %45};\n"
    "wgmma.mma_async.sync.aligned.m64n80k16.f32.bf16.bf16 {%0,%1,%2,%3,%4,%5,%6,%7,%8,%9,%10,%11,%12,%13,%14,%15,%16,%17,%18,%19,%20,%21,%22,%23,%24,%25,%26,%27,%28,%29,%30,%31,%32,%33,%34,%35,%36,%37,%38,%39}, da, db, p,1,1,1,1;\n}\n"
    : "=f"(d[0]),"=f"(d[1]),"=f"(d[2]),"=f"(d[3]),"=f"(d[4]),"=f"(d[5]),"=f"(d[6]),"=f"(d[7]),"=f"(d[8]),"=f"(d[9]),"=f"(d[10]),"=f"(d[11]),"=f"(d[12]),"=f"(d[13]),"=f"(d[14]),"=f"(d[15]),"=f"(d[16]),"=f"(d[17]),"=f"(d[18]),"=f"(d[19]),"=f"(d[20]),"=f"(d[21]),"=f"(d[22]),"=f"(d[23]),"=f"(d[24]),"=f"(d[25]),"=f"(d[26]),"=f"(d[27]),"=f"(d[28]),"=f"(d[29]),"=f"(d[30]),"=f"(d[31]),"=f"(d[32]),"=f"(d[33]),"=f"(d[34]),"=f"(d[35]),"=f"(d[36]),"=f"(d[37]),"=f"(d[38]),"=f"(d[39])
    : "r"(a),"r"(b),"n"(OA),"n"(HA),"n"(OB),"n"(HB));
}
template <int OB, uint32_t HB> __device__ __forceinline__ void mma_o88(float* d, uint32_t a0, uint32_t a1, uint32_t a2, uint32_t a3, uint32_t b) {
  asm volatile("{\n.reg .pred p;\nsetp.ne.b32 p, 1, 0;\n.reg .b32 tb;\n.reg .b64 db;\nadd.u32 tb, %48, %49;\nmov.b64 db, {tb, %50};\n"
    "wgmma.mma_async.sync.aligned.m64n88k16.f32.bf16.bf16 {%0,%1,%2,%3,%4,%5,%6,%7,%8,%9,%10,%11,%12,%13,%14,%15,%16,%17,%18,%19,%20,%21,%22,%23,%24,%25,%26,%27,%28,%29,%30,%31,%32,%33,%34,%35,%36,%37,%38,%39,%40,%41,%42,%43}, {%44,%45,%46,%47}, db, p,1,1,0;\n}\n"
    : "+f"(d[0]),"+f"(d[1]),"+f"(d[2]),"+f"(d[3]),"+f"(d[4]),"+f"(d[5]),"+f"(d[6]),"+f"(d[7]),"+f"(d[8]),"+f"(d[9]),"+f"(d[10]),"+f"(d[11]),"+f"(d[12]),"+f"(d[13]),"+f"(d[14]),"+f"(d[15]),"+f"(d[16]),"+f"(d[17]),"+f"(d[18]),"+f"(d[19]),"+f"(d[20]),"+f"(d[21]),"+f"(d[22]),"+f"(d[23]),"+f"(d[24]),"+f"(d[25]),"+f"(d[26]),"+f"(d[27]),"+f"(d[28]),"+f"(d[29]),"+f"(d[30]),"+f"(d[31]),"+f"(d[32]),"+f"(d[33]),"+f"(d[34]),"+f"(d[35]),"+f"(d[36]),"+f"(d[37]),"+f"(d[38]),"+f"(d[39]),"+f"(d[40]),"+f"(d[41]),"+f"(d[42]),"+f"(d[43])
    : "r"(a0),"r"(a1),"r"(a2),"r"(a3),"r"(b),"n"(OB),"n"(HB));
}
template <int OB, uint32_t HB> __device__ __forceinline__ void mma_o88_z(float* d, uint32_t a0, uint32_t a1, uint32_t a2, uint32_t a3, uint32_t b) {
  asm volatile("{\n.reg .pred p;\nsetp.ne.b32 p, 0, 0;\n.reg .b32 tb;\n.reg .b64 db;\nadd.u32 tb, %48, %49;\nmov.b64 db, {tb, %50};\n"
    "wgmma.mma_async.sync.aligned.m64n88k16.f32.bf16.bf16 {%0,%1,%2,%3,%4,%5,%6,%7,%8,%9,%10,%11,%12,%13,%14,%15,%16,%17,%18,%19,%20,%21,%22,%23,%24,%25,%26,%27,%28,%29,%30,%31,%32,%33,%34,%35,%36,%37,%38,%39,%40,%41,%42,%43}, {%44,%45,%46,%47}, db, p,1,1,0;\n}\n"
    : "=f"(d[0]),"=f"(d[1]),"=f"(d[2]),"=f"(d[3]),"=f"(d[4]),"=f"(d[5]),"=f"(d[6]),"=f"(d[7]),"=f"(d[8]),"=f"(d[9]),"=f"(d[10]),"=f"(d[11]),"=f"(d[12]),"=f"(d[13]),"=f"(d[14]),"=f"(d[15]),"=f"(d[16]),"=f"(d[17]),"=f"(d[18]),"=f"(d[19]),"=f"(d[20]),"=f"(d[21]),"=f"(d[22]),"=f"(d[23]),"=f"(d[24]),"=f"(d[25]),"=f"(d[26]),"=f"(d[27]),"=f"(d[28]),"=f"(d[29]),"=f"(d[30]),"=f"(d[31]),"=f"(d[32]),"=f"(d[33]),"=f"(d[34]),"=f"(d[35]),"=f"(d[36]),"=f"(d[37]),"=f"(d[38]),"=f"(d[39]),"=f"(d[40]),"=f"(d[41]),"=f"(d[42]),"=f"(d[43])
    : "r"(a0),"r"(a1),"r"(a2),"r"(a3),"r"(b),"n"(OB),"n"(HB));
}
template <int OA, uint32_t HA, int OB, uint32_t HB> __device__ __forceinline__ void mma_out80(float* d, uint32_t a, uint32_t b) {
  asm volatile("{\n.reg .pred p;\nsetp.ne.b32 p, 1, 0;\n.reg .b32 ta, tb;\n.reg .b64 da, db;\nadd.u32 ta, %40, %42;\nmov.b64 da, {ta, %43};\nadd.u32 tb, %41, %44;\nmov.b64 db, {tb, %45};\n"
    "wgmma.mma_async.sync.aligned.m64n80k16.f32.bf16.bf16 {%0,%1,%2,%3,%4,%5,%6,%7,%8,%9,%10,%11,%12,%13,%14,%15,%16,%17,%18,%19,%20,%21,%22,%23,%24,%25,%26,%27,%28,%29,%30,%31,%32,%33,%34,%35,%36,%37,%38,%39}, da, db, p,1,1,0,1;\n}\n"
    : "+f"(d[0]),"+f"(d[1]),"+f"(d[2]),"+f"(d[3]),"+f"(d[4]),"+f"(d[5]),"+f"(d[6]),"+f"(d[7]),"+f"(d[8]),"+f"(d[9]),"+f"(d[10]),"+f"(d[11]),"+f"(d[12]),"+f"(d[13]),"+f"(d[14]),"+f"(d[15]),"+f"(d[16]),"+f"(d[17]),"+f"(d[18]),"+f"(d[19]),"+f"(d[20]),"+f"(d[21]),"+f"(d[22]),"+f"(d[23]),"+f"(d[24]),"+f"(d[25]),"+f"(d[26]),"+f"(d[27]),"+f"(d[28]),"+f"(d[29]),"+f"(d[30]),"+f"(d[31]),"+f"(d[32]),"+f"(d[33]),"+f"(d[34]),"+f"(d[35]),"+f"(d[36]),"+f"(d[37]),"+f"(d[38]),"+f"(d[39])
    : "r"(a),"r"(b),"n"(OA),"n"(HA),"n"(OB),"n"(HB));
}
template <int OA, uint32_t HA, int OB, uint32_t HB> __device__ __forceinline__ void mma_kg24(float* d, uint32_t a, uint32_t b) {
  asm volatile("{\n.reg .pred p;\nsetp.ne.b32 p, 1, 0;\n.reg .b32 ta, tb;\n.reg .b64 da, db;\nadd.u32 ta, %12, %14;\nmov.b64 da, {ta, %15};\nadd.u32 tb, %13, %16;\nmov.b64 db, {tb, %17};\n"
    "wgmma.mma_async.sync.aligned.m64n24k16.f32.f16.f16 {%0,%1,%2,%3,%4,%5,%6,%7,%8,%9,%10,%11}, da, db, p,1,1,1,1;\n}\n"
    : "+f"(d[0]),"+f"(d[1]),"+f"(d[2]),"+f"(d[3]),"+f"(d[4]),"+f"(d[5]),"+f"(d[6]),"+f"(d[7]),"+f"(d[8]),"+f"(d[9]),"+f"(d[10]),"+f"(d[11])
    : "r"(a),"r"(b),"n"(OA),"n"(HA),"n"(OB),"n"(HB));
}
template <int OA, uint32_t HA, int OB, uint32_t HB> __device__ __forceinline__ void mma_kg24_z(float* d, uint32_t a, uint32_t b) {
  asm volatile("{\n.reg .pred p;\nsetp.ne.b32 p, 0, 0;\n.reg .b32 ta, tb;\n.reg .b64 da, db;\nadd.u32 ta, %12, %14;\nmov.b64 da, {ta, %15};\nadd.u32 tb, %13, %16;\nmov.b64 db, {tb, %17};\n"
    "wgmma.mma_async.sync.aligned.m64n24k16.f32.f16.f16 {%0,%1,%2,%3,%4,%5,%6,%7,%8,%9,%10,%11}, da, db, p,1,1,1,1;\n}\n"
    : "=f"(d[0]),"=f"(d[1]),"=f"(d[2]),"=f"(d[3]),"=f"(d[4]),"=f"(d[5]),"=f"(d[6]),"=f"(d[7]),"=f"(d[8]),"=f"(d[9]),"=f"(d[10]),"=f"(d[11])
    : "r"(a),"r"(b),"n"(OA),"n"(HA),"n"(OB),"n"(HB));
}
template <int OA, uint32_t HA, int OB, uint32_t HB> __device__ __forceinline__ void mma_kg48(float* d, uint32_t a, uint32_t b) {
  asm volatile("{\n.reg .pred p;\nsetp.ne.b32 p, 1, 0;\n.reg .b32 ta, tb;\n.reg .b64 da, db;\nadd.u32 ta, %24, %26;\nmov.b64 da, {ta, %27};\nadd.u32 tb, %25, %28;\nmov.b64 db, {tb, %29};\n"
    "wgmma.mma_async.sync.aligned.m64n48k16.f32.f16.f16 {%0,%1,%2,%3,%4,%5,%6,%7,%8,%9,%10,%11,%12,%13,%14,%15,%16,%17,%18,%19,%20,%21,%22,%23}, da, db, p,1,1,1,1;\n}\n"
    : "+f"(d[0]),"+f"(d[1]),"+f"(d[2]),"+f"(d[3]),"+f"(d[4]),"+f"(d[5]),"+f"(d[6]),"+f"(d[7]),"+f"(d[8]),"+f"(d[9]),"+f"(d[10]),"+f"(d[11]),"+f"(d[12]),"+f"(d[13]),"+f"(d[14]),"+f"(d[15]),"+f"(d[16]),"+f"(d[17]),"+f"(d[18]),"+f"(d[19]),"+f"(d[20]),"+f"(d[21]),"+f"(d[22]),"+f"(d[23])
    : "r"(a),"r"(b),"n"(OA),"n"(HA),"n"(OB),"n"(HB));
}
template <int OA, uint32_t HA, int OB, uint32_t HB> __device__ __forceinline__ void mma_kg48_z(float* d, uint32_t a, uint32_t b) {
  asm volatile("{\n.reg .pred p;\nsetp.ne.b32 p, 0, 0;\n.reg .b32 ta, tb;\n.reg .b64 da, db;\nadd.u32 ta, %24, %26;\nmov.b64 da, {ta, %27};\nadd.u32 tb, %25, %28;\nmov.b64 db, {tb, %29};\n"
    "wgmma.mma_async.sync.aligned.m64n48k16.f32.f16.f16 {%0,%1,%2,%3,%4,%5,%6,%7,%8,%9,%10,%11,%12,%13,%14,%15,%16,%17,%18,%19,%20,%21,%22,%23}, da, db, p,1,1,1,1;\n}\n"
    : "=f"(d[0]),"=f"(d[1]),"=f"(d[2]),"=f"(d[3]),"=f"(d[4]),"=f"(d[5]),"=f"(d[6]),"=f"(d[7]),"=f"(d[8]),"=f"(d[9]),"=f"(d[10]),"=f"(d[11]),"=f"(d[12]),"=f"(d[13]),"=f"(d[14]),"=f"(d[15]),"=f"(d[16]),"=f"(d[17]),"=f"(d[18]),"=f"(d[19]),"=f"(d[20]),"=f"(d[21]),"=f"(d[22]),"=f"(d[23])
    : "r"(a),"r"(b),"n"(OA),"n"(HA),"n"(OB),"n"(HB));
}
template <int OB, uint32_t HB> __device__ __forceinline__ void mma_cv128(float* d, uint32_t a0, uint32_t a1, uint32_t a2, uint32_t a3, uint32_t b) {
  asm volatile("{\n.reg .pred p;\nsetp.ne.b32 p, 1, 0;\n.reg .b32 tb;\n.reg .b64 db;\nadd.u32 tb, %68, %69;\nmov.b64 db, {tb, %70};\n"
    "wgmma.mma_async.sync.aligned.m64n128k16.f32.bf16.bf16 {%0,%1,%2,%3,%4,%5,%6,%7,%8,%9,%10,%11,%12,%13,%14,%15,%16,%17,%18,%19,%20,%21,%22,%23,%24,%25,%26,%27,%28,%29,%30,%31,%32,%33,%34,%35,%36,%37,%38,%39,%40,%41,%42,%43,%44,%45,%46,%47,%48,%49,%50,%51,%52,%53,%54,%55,%56,%57,%58,%59,%60,%61,%62,%63}, {%64,%65,%66,%67}, db, p,1,1,0;\n}\n"
    : "+f"(d[0]),"+f"(d[1]),"+f"(d[2]),"+f"(d[3]),"+f"(d[4]),"+f"(d[5]),"+f"(d[6]),"+f"(d[7]),"+f"(d[8]),"+f"(d[9]),"+f"(d[10]),"+f"(d[11]),"+f"(d[12]),"+f"(d[13]),"+f"(d[14]),"+f"(d[15]),"+f"(d[16]),"+f"(d[17]),"+f"(d[18]),"+f"(d[19]),"+f"(d[20]),"+f"(d[21]),"+f"(d[22]),"+f"(d[23]),"+f"(d[24]),"+f"(d[25]),"+f"(d[26]),"+f"(d[27]),"+f"(d[28]),"+f"(d[29]),"+f"(d[30]),"+f"(d[31]),"+f"(d[32]),"+f"(d[33]),"+f"(d[34]),"+f"(d[35]),"+f"(d[36]),"+f"(d[37]),"+f"(d[38]),"+f"(d[39]),"+f"(d[40]),"+f"(d[41]),"+f"(d[42]),"+f"(d[43]),"+f"(d[44]),"+f"(d[45]),"+f"(d[46]),"+f"(d[47]),"+f"(d[48]),"+f"(d[49]),"+f"(d[50]),"+f"(d[51]),"+f"(d[52]),"+f"(d[53]),"+f"(d[54]),"+f"(d[55]),"+f"(d[56]),"+f"(d[57]),"+f"(d[58]),"+f"(d[59]),"+f"(d[60]),"+f"(d[61]),"+f"(d[62]),"+f"(d[63])
    : "r"(a0),"r"(a1),"r"(a2),"r"(a3),"r"(b),"n"(OB),"n"(HB));
}
template <int OB, uint32_t HB> __device__ __forceinline__ void mma_cv128_z(float* d, uint32_t a0, uint32_t a1, uint32_t a2, uint32_t a3, uint32_t b) {
  asm volatile("{\n.reg .pred p;\nsetp.ne.b32 p, 0, 0;\n.reg .b32 tb;\n.reg .b64 db;\nadd.u32 tb, %68, %69;\nmov.b64 db, {tb, %70};\n"
    "wgmma.mma_async.sync.aligned.m64n128k16.f32.bf16.bf16 {%0,%1,%2,%3,%4,%5,%6,%7,%8,%9,%10,%11,%12,%13,%14,%15,%16,%17,%18,%19,%20,%21,%22,%23,%24,%25,%26,%27,%28,%29,%30,%31,%32,%33,%34,%35,%36,%37,%38,%39,%40,%41,%42,%43,%44,%45,%46,%47,%48,%49,%50,%51,%52,%53,%54,%55,%56,%57,%58,%59,%60,%61,%62,%63}, {%64,%65,%66,%67}, db, p,1,1,0;\n}\n"
    : "=f"(d[0]),"=f"(d[1]),"=f"(d[2]),"=f"(d[3]),"=f"(d[4]),"=f"(d[5]),"=f"(d[6]),"=f"(d[7]),"=f"(d[8]),"=f"(d[9]),"=f"(d[10]),"=f"(d[11]),"=f"(d[12]),"=f"(d[13]),"=f"(d[14]),"=f"(d[15]),"=f"(d[16]),"=f"(d[17]),"=f"(d[18]),"=f"(d[19]),"=f"(d[20]),"=f"(d[21]),"=f"(d[22]),"=f"(d[23]),"=f"(d[24]),"=f"(d[25]),"=f"(d[26]),"=f"(d[27]),"=f"(d[28]),"=f"(d[29]),"=f"(d[30]),"=f"(d[31]),"=f"(d[32]),"=f"(d[33]),"=f"(d[34]),"=f"(d[35]),"=f"(d[36]),"=f"(d[37]),"=f"(d[38]),"=f"(d[39]),"=f"(d[40]),"=f"(d[41]),"=f"(d[42]),"=f"(d[43]),"=f"(d[44]),"=f"(d[45]),"=f"(d[46]),"=f"(d[47]),"=f"(d[48]),"=f"(d[49]),"=f"(d[50]),"=f"(d[51]),"=f"(d[52]),"=f"(d[53]),"=f"(d[54]),"=f"(d[55]),"=f"(d[56]),"=f"(d[57]),"=f"(d[58]),"=f"(d[59]),"=f"(d[60]),"=f"(d[61]),"=f"(d[62]),"=f"(d[63])
    : "r"(a0),"r"(a1),"r"(a2),"r"(a3),"r"(b),"n"(OB),"n"(HB));
}
template <int OB, uint32_t HB> __device__ __forceinline__ void mma_cv64(float* d, uint32_t a0, uint32_t a1, uint32_t a2, uint32_t a3, uint32_t b) {
  asm volatile("{\n.reg .pred p;\nsetp.ne.b32 p, 1, 0;\n.reg .b32 tb;\n.reg .b64 db;\nadd.u32 tb, %36, %37;\nmov.b64 db, {tb, %38};\n"
    "wgmma.mma_async.sync.aligned.m64n64k16.f32.bf16.bf16 {%0,%1,%2,%3,%4,%5,%6,%7,%8,%9,%10,%11,%12,%13,%14,%15,%16,%17,%18,%19,%20,%21,%22,%23,%24,%25,%26,%27,%28,%29,%30,%31}, {%32,%33,%34,%35}, db, p,1,1,0;\n}\n"
    : "+f"(d[0]),"+f"(d[1]),"+f"(d[2]),"+f"(d[3]),"+f"(d[4]),"+f"(d[5]),"+f"(d[6]),"+f"(d[7]),"+f"(d[8]),"+f"(d[9]),"+f"(d[10]),"+f"(d[11]),"+f"(d[12]),"+f"(d[13]),"+f"(d[14]),"+f"(d[15]),"+f"(d[16]),"+f"(d[17]),"+f"(d[18]),"+f"(d[19]),"+f"(d[20]),"+f"(d[21]),"+f"(d[22]),"+f"(d[23]),"+f"(d[24]),"+f"(d[25]),"+f"(d[26]),"+f"(d[27]),"+f"(d[28]),"+f"(d[29]),"+f"(d[30]),"+f"(d[31])
    : "r"(a0),"r"(a1),"r"(a2),"r"(a3),"r"(b),"n"(OB),"n"(HB));
}
template <int OB, uint32_t HB> __device__ __forceinline__ void mma_cv64_z(float* d, uint32_t a0, uint32_t a1, uint32_t a2, uint32_t a3, uint32_t b) {
  asm volatile("{\n.reg .pred p;\nsetp.ne.b32 p, 0, 0;\n.reg .b32 tb;\n.reg .b64 db;\nadd.u32 tb, %36, %37;\nmov.b64 db, {tb, %38};\n"
    "wgmma.mma_async.sync.aligned.m64n64k16.f32.bf16.bf16 {%0,%1,%2,%3,%4,%5,%6,%7,%8,%9,%10,%11,%12,%13,%14,%15,%16,%17,%18,%19,%20,%21,%22,%23,%24,%25,%26,%27,%28,%29,%30,%31}, {%32,%33,%34,%35}, db, p,1,1,0;\n}\n"
    : "=f"(d[0]),"=f"(d[1]),"=f"(d[2]),"=f"(d[3]),"=f"(d[4]),"=f"(d[5]),"=f"(d[6]),"=f"(d[7]),"=f"(d[8]),"=f"(d[9]),"=f"(d[10]),"=f"(d[11]),"=f"(d[12]),"=f"(d[13]),"=f"(d[14]),"=f"(d[15]),"=f"(d[16]),"=f"(d[17]),"=f"(d[18]),"=f"(d[19]),"=f"(d[20]),"=f"(d[21]),"=f"(d[22]),"=f"(d[23]),"=f"(d[24]),"=f"(d[25]),"=f"(d[26]),"=f"(d[27]),"=f"(d[28]),"=f"(d[29]),"=f"(d[30]),"=f"(d[31])
    : "r"(a0),"r"(a1),"r"(a2),"r"(a3),"r"(b),"n"(OB),"n"(HB));
}

template <int H>
__device__ __forceinline__ void dual_softmax(const float* acc, uint32_t* out) {
  constexpr float L2E = 1.4426950408889634f;
  float mx = fmaxf(acc[2 * H], acc[2 * H + 1]);
#pragma unroll
  for (int b = 1; b < 10; b++) mx = fmaxf(mx, fmaxf(acc[4 * b + 2 * H], acc[4 * b + 2 * H + 1]));
  const float mxl = -mx * L2E;
  float e[20];
  float s0 = 0.f, s1 = 0.f;
#pragma unroll
  for (int i = 0; i < 10; i++) {
    e[2 * i] = ex2(fmaf(acc[4 * i + 2 * H], L2E, mxl));
    e[2 * i + 1] = ex2(fmaf(acc[4 * i + 2 * H + 1], L2E, mxl));
    s0 += e[2 * i];
    s1 += e[2 * i + 1];
  }
  const float ra = rcp(s0 + s1);
  s0 = s1 = 0.f;
#pragma unroll
  for (int i = 0; i < 10; i++) {
    out[i] = pack_bf16(e[2 * i] * ra, e[2 * i + 1] * ra);
    const float r = rcp(e[2 * i] * e[2 * i + 1]), a = e[2 * i];
    e[2 * i] = e[2 * i + 1] * r;
    e[2 * i + 1] = a * r;
    s0 += e[2 * i];
    s1 += e[2 * i + 1];
  }
  if (__builtin_expect(!(s0 + s1 < 1e37f), 0)) {
    float mn = fminf(acc[2 * H], acc[2 * H + 1]);
#pragma unroll
    for (int b = 1; b < 10; b++) mn = fminf(mn, fminf(acc[4 * b + 2 * H], acc[4 * b + 2 * H + 1]));
    const float mnl = mn * L2E;
    s0 = s1 = 0.f;
#pragma unroll
    for (int i = 0; i < 10; i++) {
      e[2 * i] = ex2(fmaf(acc[4 * i + 2 * H], -L2E, mnl));
      e[2 * i + 1] = ex2(fmaf(acc[4 * i + 2 * H + 1], -L2E, mnl));
      s0 += e[2 * i];
      s1 += e[2 * i + 1];
    }
  }
  const float rb = rcp(s0 + s1);
#pragma unroll
  for (int i = 0; i < 10; i++) out[10 + i] = pack_bf16(e[2 * i] * rb, e[2 * i + 1] * rb);
}

struct Cx { float re, im; };
__device__ __forceinline__ Cx cmul(Cx a, Cx b) { return Cx{fmaf(a.re, b.re, -a.im * b.im), fmaf(a.re, b.im, a.im * b.re)}; }
__device__ __forceinline__ Cx cexp_e(float za, float zi, float e) {
  const float m = ex2(za * e);
  const float ph = zi * e;
  const float k = __fadd_rn(__fmaf_rn(ph, 0.15915494f, 12582912.f), -12582912.f);
  float r = fmaf(ph, 0.15915494f, -k);
  r = fmaf(ph, 6.4206382e-9f, r);
  r *= 6.2831853071795865f;
  return Cx{m * __cosf(r), m * __sinf(r)};
}

__device__ __forceinline__ Cx csqr(Cx a) { return Cx{fmaf(a.re, a.re, -a.im * a.im), (a.re + a.re) * a.im}; }
struct Hp { uint32_t re, im; };
__device__ __forceinline__ Hp planar(Cx a, Cx b) { return Hp{pack_f16(a.re, b.re), pack_f16(a.im, b.im)}; }
__device__ __forceinline__ Hp hpmul(Hp x, uint32_t y) {
  const __half2 Y = *reinterpret_cast<const __half2*>(&y), R = *reinterpret_cast<const __half2*>(&x.re), I = *reinterpret_cast<const __half2*>(&x.im);
  const __half2 r = __hfma2(__hneg2(I), __high2half2(Y), __hmul2(R, __low2half2(Y)));
  const __half2 i = __hfma2(R, __high2half2(Y), __hmul2(I, __low2half2(Y)));
  return Hp{*reinterpret_cast<const uint32_t*>(&r), *reinterpret_cast<const uint32_t*>(&i)};
}

struct Anchors { Hp e46, b4, b8, xb; uint32_t e1, e2, x1, b2, b16, y[8]; };
constexpr int NANCH = 21;
__device__ __forceinline__ void ssm_anchors(float za, float zi, Cx cs, Anchors& a) {
  const Cx e1 = cexp_e(za, -zi, 1.f), b2 = cexp_e(za, -zi, 256.f), x1 = cexp_e(za, zi, 8.f);
  const Cx e2 = csqr(e1), e4 = csqr(e2), e6 = cmul(e4, e2);
  const Cx b4 = csqr(b2), b8 = csqr(b4), b12 = cmul(b8, b4), b16 = csqr(b8), b4e = cmul(b4, e4);
  a.e1 = pack_f16(e1.re, e1.im); a.e2 = pack_f16(e2.re, e2.im); a.e46 = planar(e4, e6);
  a.b2 = pack_f16(b2.re, b2.im); a.b4 = planar(b4, b4e); a.b8 = planar(b8, b12); a.b16 = pack_f16(b16.re, b16.im);
  const Cx x2 = csqr(x1), x3 = cmul(x2, x1), x4 = csqr(x2);
  a.x1 = pack_f16(x1.re, x1.im);
  a.xb = planar(x2, x3);
  Cx y = cs;
#pragma unroll
  for (int j = 0; j < 8; j++) {
    a.y[j] = pack_f16(y.re, y.im);
    if (j < 7) y = cmul(y, x4);
  }
}
__device__ __forceinline__ Hp one_and(uint32_t v) { return Hp{__byte_perm(0x3C00u, v, 0x5410), v & 0xffff0000u}; }
__device__ __forceinline__ void put_factors(uint32_t tab, int t, Hp v0, Hp v1, Hp v2, Hp v3) {
  const uint32_t a = tab + (t >> 2) * 128 + (t & 4) * 16 + (t & 3) * 16;
  sts128(a, v0.re, v1.re, v2.re, v3.re);
  sts128(a ^ 64, v0.im, v1.im, v2.im, v3.im);
}
__device__ __forceinline__ void store_factors(const Anchors& a, uint32_t rows, uint32_t cols, int t) {
  const Hp e02 = one_and(a.e2), xa = one_and(a.x1);
  put_factors(cols, t, e02, a.e46, hpmul(e02, a.e1), hpmul(a.e46, a.e1));
  put_factors(cols + 4096, t, hpmul(e02, a.b2), hpmul(a.e46, a.b2), a.b4, hpmul(a.b4, a.b2));
  put_factors(cols + 8192, t, a.b8, hpmul(a.b8, a.b2), Hp{a.b16 & 0xffffu, a.b16 >> 16}, Hp{0u, 0u});
#pragma unroll
  for (int i = 0; i < 4; i++)
    put_factors(rows + i * 4096, t, hpmul(xa, a.y[2 * i]), hpmul(a.xb, a.y[2 * i]), hpmul(xa, a.y[2 * i + 1]), hpmul(a.xb, a.y[2 * i + 1]));
}
__device__ __forceinline__ void ssm_gemm(float* kd, uint32_t tab) {
  const uint32_t d = dlo(tab, 128);
  constexpr uint32_t H = dhi(4096, 0);
  mma_kg24_z<0, H, 1024, H>(kd, d, d);
  static_for<1, 16>([&](auto k) { mma_kg24<k * 16, H, 1024 + k * 16, H>(kd, d, d); });
  wg_commit();
}
__device__ __forceinline__ void ssm_gemm2(float* kd, uint32_t rows, uint32_t cols) {
  const uint32_t da = dlo(rows, 128), db = dlo(cols, 128);
  constexpr uint32_t H = dhi(4096, 0);
  mma_kg48_z<0, H, 0, H>(kd, da, db);
  static_for<1, 16>([&](auto k) { mma_kg48<k * 16, H, k * 16, H>(kd, da, db); });
  wg_commit();
}

__device__ __forceinline__ void store_taps(const float* kd, float unscale, float dskip, uint32_t kz, int t) {
  {
    const int q = t & 3, i = (t >> 5) * 16 + ((t & 31) >> 2);
    const bool lo = q < 2;
    const uint32_t a0 = kz + (8 * i + 4 * (q & 1) + (q >> 1)) * 2, a1 = kz + 512 + (lo ? 8 * i + 4 * q : 128 * q + 4 * i);
    const uint32_t a2 = kz + (lo ? 1024 + 64 * q + 2 * i : 1284), a3 = kz + (lo ? 1152 + 64 * q + 2 * i : 1284);
#pragma unroll
    for (int h = 0; h < 2; h++) {
      const uint32_t w0 = pack_bf16(fmaf(kd[2 * h], unscale, (h == 0 && t == 0) ? dskip : 0.f), kd[2 * h + 1] * unscale);
      const uint32_t w2 = pack_bf16(kd[8 + 2 * h] * unscale, kd[9 + 2 * h] * unscale);
      sts16(a0 + 128 * h, w0 & 0xffffu);
      sts16(a0 + 128 * h + 4, w0 >> 16);
      sts32(a1 + (h ? (lo ? 64 : 32) : 0), pack_bf16(kd[4 + 2 * h] * unscale, kd[5 + 2 * h] * unscale));
      sts16(h ? a2 + (lo ? 16 : 0) : t == 2 ? kz + 1280 : a2, w2 & 0xffffu);
      sts16(h ? a3 + (lo ? 16 : 0) : a3, w2 >> 16);
    }
  }
}

template <int N>
__device__ __forceinline__ void build_taps(uint32_t kz, uint32_t pt, int t0, int step) {
  uint32_t w[N], wm[N], v0[N], vm[N], vp[N], a[N][2], b[N][2];
#pragma unroll
  for (int n = 0; n < N; n++) {
    const int t = t0 + n * step, odd = t & 1;
    w[n] = lds32(kz + t * 4);
    wm[n] = lds16(kz + t * 4 - (t ? 2 : 0));
    v0[n] = lds16(kz + (256 + t) * 2);
    vm[n] = lds16(kz + (256 + t - odd) * 2);
    vp[n] = lds16(kz + (256 + t + odd) * 2);
#pragma unroll
    for (int i = 0; i < 2; i++) {
      a[n][i] = lds16(kz + (384 + 64 * i + (t >> 1)) * 2);
      b[n][i] = lds16(kz + (385 + 64 * i + (t >> 1)) * 2);
    }
  }
  uint32_t s = 0, k0 = 0, k1 = 0, k2 = 0;
  if (t0 < 3) { s = lds16(kz + 1024); k0 = lds16(kz + 510); k1 = lds16(kz + 768); k2 = lds16(kz + 896); }
#pragma unroll
  for (int n = 0; n < N; n++) {
    const int t = t0 + n * step;
    const uint32_t hi_mask = t ? 0xffffffffu : 0x0000ffffu;
    sts128(pt + 128 + t * 16, __byte_perm(w[n], wm[n], 0x5410) & hi_mask, __byte_perm(v0[n], vm[n], 0x5410) & hi_mask,
           __byte_perm(w[n], w[n], 0x1032), __byte_perm(vp[n], v0[n], 0x5410));
    uint32_t t0w[2], t1w[2];
#pragma unroll
    for (int i = 0; i < 2; i++) {
      const uint32_t mid = (t & 3) == 3 ? b[n][i] : a[n][i], hi = (t & 1) ? b[n][i] : a[n][i];
      t0w[i] = __byte_perm(mid, a[n][i], 0x5410) & hi_mask;
      t1w[i] = __byte_perm(hi, mid, 0x5410);
    }
    sts128(pt + 2432 + 128 + t * 16, t0w[0], t0w[1], t1w[0], t1w[1]);
  }
  if (t0 < 3) {
    const uint32_t ss = s | (s << 16);
    if (t0 == 0) sts64(pt + 128 + 2048, k0 << 16, k1 << 16);
    sts128(pt + 2432 + 128 + 2048 + t0 * 16, t0 ? 0u : k2 << 16, ss, 0u, t0 == 2 ? s << 16 : ss);
  }
}
template <int N>
__device__ __forceinline__ void build_far_taps(uint32_t kz, uint32_t hh, int t0, int step) {
  uint32_t hv[N][8];
#pragma unroll
  for (int n = 0; n < N; n++) {
    const int t = t0 + n * step, om = t & 63;
    const uint32_t hb = kz + (513 + (t >> 6) + 2 * om) * 2;
#pragma unroll
    for (int i = 0; i < 8; i++) hv[n][i] = lds16(hb - 4 * i);
  }
#pragma unroll
  for (int n = 0; n < N; n++) {
    const int t = t0 + n * step, om = t & 63;
    uint32_t o[4];
#pragma unroll
    for (int i = 0; i < 4; i++) o[i] = om > 2 * i ? __byte_perm(hv[n][2 * i], hv[n][2 * i + 1], 0x5410) : om == 2 * i ? hv[n][2 * i] : 0u;
    sts128(hh + (t >> 6) * 2176 + (72 + om) * 16, o[0], o[1], o[2], o[3]);
  }
}

__device__ __forceinline__ void build_bands(uint32_t dst, int t) {
  const int b = (t >> 2) & 15, k = 2 * (t & 3);
#pragma unroll
  for (int s = 0; s < 3; s++) {
    uint32_t f[4];
#pragma unroll
    for (int i = 0; i < 4; i++) {
      const int d = k + 8 * (i >> 1) - 16 * s - b, lo = (i & 1) ? -20 : -11, hi = (i & 1) ? -12 : -5;
      f[i] = (d >= lo && d <= hi ? 0x3F80u : 0u) | (d + 1 >= lo && d + 1 <= hi ? 0x3F800000u : 0u);
    }
    sts128(dst + s * 1024 + t * 16, f[0], f[1], f[2], f[3]);
  }
}

__device__ __forceinline__ void load_frag(uint32_t* r, uint32_t a) {
  const uint2 x = lds64(a), y = lds64(a - 64);
  r[0] = x.x; r[1] = x.y; r[2] = y.x; r[3] = y.y;
}

__device__ __forceinline__ void conv_mma(float* y, uint32_t bands, uint32_t ub, uint32_t pt, uint32_t hh, uint32_t bar_free, int wp, int lane) {
  const int r = wp >> 1, p = wp & 1;
  uint32_t fr[4][4];
  const uint32_t pa = pt + p * 2432 + (16 + 8 * r + (lane >> 2) - 2 * (lane & 3)) * 8;
  const uint32_t dU = dlo(ub, 16), dH = dlo(hh, 128);
  constexpr uint32_t HC = dhi(128, 0), HU = dhi(256, 3);
  {
    float ws[32];
#pragma unroll
    for (int i = 0; i < 3; i++) {
      const uint4 v = lds128(bands + i * 1024 + r * 512 + lane * 16);
      fr[i][0] = v.x; fr[i][1] = v.y; fr[i][2] = v.z; fr[i][3] = v.w;
    }
    wg_fence();
    mma_cv64_z<2 * UB_Z, HU>(ws, fr[0][0], fr[0][1], fr[0][2], fr[0][3], dU);
    mma_cv64<2 * UB_Z - 2, HU>(ws, fr[1][0], fr[1][1], fr[1][2], fr[1][3], dU);
    mma_cv64<2 * UB_Z - 4, HU>(ws, fr[2][0], fr[2][1], fr[2][2], fr[2][3], dU);
    wg_commit();
    wg_wait<0>();
    pin<32>(ws);
    pin<12>(&fr[0][0]);
    load_frag(fr[0], pa);
    load_frag(fr[1], pa + 128);
#pragma unroll
    for (int i = 0; i < 4; i++) {
      const int b = ((i & 1) << 1) | (1 - (i >> 1));
      fr[2][i] = pack_bf16(p ? ws[16 + 4 * b] : ws[4 * b], p ? ws[17 + 4 * b] : ws[4 * b + 1]);
      fr[3][i] = pack_bf16(p ? ws[18 + 4 * b] : ws[4 * b + 2], p ? ws[19 + 4 * b] : ws[4 * b + 3]);
    }
  }
  wg_fence();
  mma_cv128_z<0, HC>(y, fr[2][0], fr[2][1], fr[2][2], fr[2][3], dH);
  wg_commit();
  mma_cv128<136, HC>(y, fr[3][0], fr[3][1], fr[3][2], fr[3][3], dH);
  wg_commit();
  static_for<0, 18>([&](auto jc) {
    constexpr int j = jc;
    uint32_t* f = fr[j & 3];
    wg_fence();
    mma_cv128<2 * (UB_Z - j), HU>(y, f[0], f[1], f[2], f[3], dU);
    wg_commit();
    if (j + 2 < 18) {
      wg_wait<2>();
      pin<4>(fr[(j + 2) & 3]);
      load_frag(fr[(j + 2) & 3], pa + (j + 2) * 128);
    }
    if (j == 1 && bar_free && lane == 0) mbar_arrive(bar_free);
  });
  wg_wait<0>();
  pin<64>(y);
  pin<16>(&fr[0][0]);
#pragma unroll
  for (int b = 15; b >= 2; b--) { y[4 * b] += y[4 * b - 6]; y[4 * b + 1] += y[4 * b - 5]; }
}
__device__ __forceinline__ void conv_store(int bar, const float* y, uint32_t x1, uint32_t x2, uint32_t* yd, int wp, int lane) {
  const int r = wp >> 1, p = wp & 1;
  x1 += r * 512 + lane * 16;
  x2 += r * 512 + lane * 16;
  if (p == 0) {
#pragma unroll
    for (int i = 0; i < 4; i++)
      sts128(x1 + i * 1024, __float_as_uint(y[32 + 8 * i]), __float_as_uint(y[33 + 8 * i]), __float_as_uint(y[36 + 8 * i]), __float_as_uint(y[37 + 8 * i]));
  } else {
#pragma unroll
    for (int i = 0; i < 2; i++)
      sts128(x2 + i * 1024, __float_as_uint(y[8 * i]), __float_as_uint(y[8 * i + 1]), __float_as_uint(y[8 * i + 4]), __float_as_uint(y[8 * i + 5]));
  }
  asm volatile("bar.sync %0, 128;" ::"r"(bar) : "memory");
  float z[16];
#pragma unroll
  for (int i = 0; i < 8; i++) { z[2 * i] = p ? y[16 + 4 * i] : y[4 * i]; z[2 * i + 1] = p ? y[17 + 4 * i] : y[4 * i + 1]; }
  if (p == 0) {
    const uint4 v0 = lds128(x2), v1 = lds128(x2 + 1024);
    z[8] += __uint_as_float(v0.x); z[9] += __uint_as_float(v0.y); z[10] += __uint_as_float(v0.z); z[11] += __uint_as_float(v0.w);
    z[12] += __uint_as_float(v1.x); z[13] += __uint_as_float(v1.y); z[14] += __uint_as_float(v1.z); z[15] += __uint_as_float(v1.w);
  } else {
#pragma unroll
    for (int i = 0; i < 4; i++) {
      const uint4 v = lds128(x1 + i * 1024);
      z[4 * i] += __uint_as_float(v.x); z[4 * i + 1] += __uint_as_float(v.y); z[4 * i + 2] += __uint_as_float(v.z); z[4 * i + 3] += __uint_as_float(v.w);
    }
  }
  yd += (lane & 3) * 16 + 8 * r + (lane >> 2) + p * 512;
#pragma unroll
  for (int i = 0; i < 8; i++) yd[i * 64] = pack_bf16(z[2 * i], z[2 * i + 1]);
  __syncwarp();
}

__device__ __forceinline__ void transpose_store(const uint4* L, uint4* dst, int stride) {
  dst[0] = make_uint4(movm(L[0].x), movm(L[1].x), movm(L[2].x), movm(L[3].x));
  dst[stride] = make_uint4(movm(L[0].y), movm(L[1].y), movm(L[2].y), movm(L[3].y));
  dst[2 * stride] = make_uint4(movm(L[0].z), movm(L[1].z), movm(L[2].z), movm(L[3].z));
  dst[3 * stride] = make_uint4(movm(L[0].w), movm(L[1].w), movm(L[2].w), movm(L[3].w));
}

#define LANE_IDS                                           \
  int tid_;                                                \
  asm volatile("mov.u32 %0, %%tid.x;" : "=r"(tid_));       \
  const int lane = tid_ & 31, wp = (tid_ >> 5) & 3, g = lane >> 2, q = lane & 3; \
  (void)wp; (void)g; (void)q;
#define ROW_IDS LANE_IDS const int row = (tid_ >> 5) * 16 + g;

__global__ void __launch_bounds__(512, 1) fused_kernel(const __grid_constant__ Params P) {
  extern __shared__ __align__(1024) uint8_t smem_raw[];
  const uint32_t sb = (uint32_t)__cvta_generic_to_shared(smem_raw);
  const int tid = threadIdx.x;
  unsigned smid;
  asm("mov.u32 %0, %%smid;" : "=r"(smid));
  const int cta = P.tile_of_sm[smid < 192 ? smid : 191];
  if (cta >= NCTA) {
    if (tid == 0) wait_count(CNT_START, (atomicAdd(&g_cnt[CNT_START * 32], 1u) / P.nsm + 1) * P.nsm);
    return;
  }
  const int rb = cta >> 3;
  const int hg = cta & 7;

  if (tid == 384) {
    mbar_init(sb + BAR_FULL, 1);
    asm volatile("fence.mbarrier_init.release.cluster;" ::: "memory");
    mbar_expect(sb + BAR_FULL, STAGE);
    tma2d(sb, &P.x, sb + BAR_FULL, 0, rb * 128);
    tma3d(sb + OFF_W128, &P.w128, sb + BAR_FULL, hg * 80, 0, 0);
    tma3d(sb + OFF_W16, &P.w16, sb + BAR_FULL, hg * 80 + 64, 0, 0);
    STAMP(46);
  } else if ((tid & 31) == 0 && (tid < 256 || tid > 384)) {
    const int w = tid < 256 ? tid >> 5 : (tid >> 5) - 5;
#pragma unroll
    for (int i = 0; i < 3; i++) mbar_init(sb + SM_MISC + 8 * (1 + 3 * w + i), P.bar_count[1 + 3 * w + i]);
    if (w == 10) mbar_init(sb + BAR_KVB, 1);
    if (w == 9) mbar_init(sb + BAR_CV, 12);
    if (w == 8) mbar_init(sb + BAR_AXF, 1);
    if (w == 7) mbar_init(sb + BAR_RD4, 96);
    if (w == 6) mbar_init(sb + BAR_CVA, 4);
    if (w == 5) mbar_init(sb + BAR_RD3, 96);
    asm volatile("fence.mbarrier_init.release.cluster;" ::: "memory");
  }
  uint32_t raw[3][6], rawc = 0;
  if (tid >= 256 && tid < 384) {
#pragma unroll
    for (int c = 0; c < 2; c++)
#pragma unroll
      for (int i = 0; i < 6; i++) raw[c][i] = __ldg(P.ssm[i] + cta * 640 + c * 128 + tid - 256);
    const int l = tid & 31;
    if (l < 10) rawc = __ldg((l < 5 ? P.logdt : P.dskip - 5) + cta * 5 + l);
  }
  __syncthreads();

  if (tid >= 384) {
    asm volatile("setmaxnreg.dec.sync.aligned.u32 56;");
    LANE_IDS
    if (wp == 0) {
      bool wo_late = false;
      if (lane == 0) {
        STAMP(40);
#pragma unroll 1
        for (int it = 1; it < 10; it++) {
          const int s = it & 3;
          if (it >= 4) mbar_wait(sb + BAR_EMPTY + 8 * s, ((it >> 2) - 1) & 1);
          const uint32_t d = sb + s * STAGE, fb = sb + BAR_FULL + 8 * s;
          mbar_expect(fb, STAGE);
          tma2d(d, &P.x, fb, it * 64, rb * 128);
          tma3d(d + OFF_W128, &P.w128, fb, hg * 80, it * 64, 0);
          tma3d(d + OFF_W16, &P.w16, fb, hg * 80 + 64, it * 64, 0);
          if (it == 3) {
            mbar_expect(sb + BAR_PRM, 4608);
#pragma unroll 1
            for (int i = 0; i < 6; i++)
              asm volatile("cp.async.bulk.shared::cluster.global.mbarrier::complete_tx::bytes [%0], [%1], 768, [%2];" ::"r"(sb + SM_UB0 + i * 768), "l"(P.ssm[i] + cta * 640 + 256), "r"(sb + BAR_PRM) : "memory");
            mbar_expect(sb + BAR_WP, 3200);
            asm volatile("cp.async.bulk.shared::cluster.global.mbarrier::complete_tx::bytes [%0], [%1], 3200, [%2];" ::"r"(sb + SM_WP), "l"(P.wphi + hg * 800), "r"(sb + BAR_WP) : "memory");
          }
        }
        mbar_expect(sb + BAR_WO, 102400);
        mbar_wait(sb + BAR_MAIN, 0);
#pragma unroll 1
        for (int j = 0; j < 6; j++) {
          if (j == 5) mbar_wait(sb + BAR_PHI, 0);
          const int i = j < 4 ? j + 6 : 5 * (j - 4);
          tma3d(sb + SM_WO + i * 10240, &P.wo, sb + BAR_WO, 0, i * 64, hg * 5);
        }
        wo_late = !mbar_test(sb + BAR_KGD, 0);
        if (!wo_late) {
#pragma unroll 1
          for (int i = 1; i < 5; i++) tma3d(sb + SM_WO + i * 10240, &P.wo, sb + BAR_WO, 0, i * 64, hg * 5);
        }
        mbar_wait(sb + BAR_EPOCH, 0);
      }
      __syncwarp();
      const unsigned epoch = lds32(sb + SM_EPOCH);
      bar_sync<4, 288>();
      if (lane == 0) {
        asm volatile("cp.reduce.async.bulk.global.shared::cta.bulk_group.add.f32 [%0], [%1], 14400;" ::"l"(g_kv + (epoch & 1) * 28800 + hg * 3600), "r"(sb + SM_KVST) : "memory");
        bulk_commit_wait();
        mbar_arrive(sb + BAR_AXF);
        STAMP(42);
        signal(CNT_KV + hg);
        STAMP(43);
        if (wo_late) {
          mbar_wait(sb + BAR_KGD, 0);
          mbar_wait(sb + BAR_KVB, 0);
#pragma unroll 1
          for (int i = 1; i < 5; i++) tma3d(sb + SM_WO + i * 10240, &P.wo, sb + BAR_WO, 0, i * 64, hg * 5);
        }
      }
      __syncwarp();
      bar_sync<5, 288>();
      if (lane == 0) {
        tma2d_store(&P.ost, sb + SM_OST, hg * 80, rb * 128);
        bulk_commit_wait();
        STAMP(44);
        signal(CNT_O + rb);
        STAMP(45);
        wait_count(CNT_O + rb, (epoch + 1) * 8);
        fence_async_global();
        STAMP(41);
#pragma unroll 1
        for (int j = 0; j < 10; j++) {
          const int it = j == 3 ? 4 : j == 4 ? 3 : j, s = it < 5 ? it : it - 5;
          if (it == 3) mbar_wait(sb + BAR_CVA, 0);
          if (it >= 5) mbar_wait(sb + BAR_OEMPTY + 8 * s, 0);
          mbar_expect(sb + BAR_OFULL + 8 * s, 16384);
          tma2d(sb + (s < 4 ? s * 16384 : SM_O4), &P.o, sb + BAR_OFULL + 8 * s, it * 64, rb * 128);
        }
      }
    } else {
      const int ht = tid_ - 416;
      if (wp == 3 && lane < 4) asm volatile("prefetch.tensormap [%0];" ::"l"(&P.wo + lane) : "memory");
      if (wp == 1) {
        unsigned epoch = 0;
        if (lane == 0) {
          epoch = atomicAdd(&g_cnt[CNT_START * 32], 1u) / P.nsm;
          sts32(sb + SM_EPOCH, epoch);
          mbar_arrive(sb + BAR_EPOCH);
        }
        epoch = __shfl_sync(0xffffffffu, epoch, 0);
        float4* z = reinterpret_cast<float4*>(g_kv + ((epoch + 1) & 1) * 28800 + hg * 3600);
#pragma unroll 1
        for (int i = rb * 57 + lane; i < min(rb * 57 + 57, 900); i += 32) z[i] = make_float4(0.f, 0.f, 0.f, 0.f);
      }
      mbar_wait(sb + BAR_FULL, 0);
      {
        const int r0 = 64 * (cta & 31), c0 = 160 * (cta >> 5) + 32 * (wp - 1), gr = 8 * (g >> 1) + (g & 1);
        const uint4* src = reinterpret_cast<const uint4*>(P.u + (r0 + gr) * 640 + c0 + 8 * q);
        uint4* dst = reinterpret_cast<uint4*>(g_uT + (c0 + gr) * 2048 + r0 + 8 * (q ^ (cta & 1)));
#pragma unroll 1
        for (int hi = 0; hi < 2; hi++, src += 2560, dst += 4) {
          uint4 L0[4], L1[4];
#pragma unroll
          for (int j = 0; j < 4; j++) L0[j] = __ldg(src + j * 160);
          if (wp < 3) {
#pragma unroll
            for (int j = 0; j < 4; j++) L1[j] = __ldg(src + j * 160 + 12);
          }
          transpose_store(L0, dst, 512);
          if (wp < 3) transpose_store(L1, dst + 96 * 256, 512);
        }
      }
      if (wp == 2) {
        bar_sync<6, 96>();
        STAMP_IF(lane == 0, 49);
        if (lane == 0) {
          signal(CNT_T1 + (cta >> 5));
          STAMP(47);
          mbar_wait(sb + BAR_EPOCH, 0);
          wait_count(CNT_T1 + (cta >> 5), (lds32(sb + SM_EPOCH) + 1) * 32);
          fence_async_global();
          STAMP(36);
          mbar_wait(sb + BAR_PRF, 0);
          mbar_expect(sb + BAR_UB, 4096);
          bulk_load(sb + SM_UB0 + UB_Z * 32, g_uT + (cta * 5) * 2048, 4096, sb + BAR_UB);
        }
        __syncwarp();
      } else {
        bar_arrive<6, 96>();
        mbar_wait(sb + BAR_WP, 0);
        mbar_wait(sb + BAR_S6, 0);
#pragma unroll 1
        for (int b = wp >> 1; b < 10; b += 2) {
          uint32_t w[3];
#pragma unroll
          for (int i = 0; i < 3; i++) w[i] = lds32(sb + SM_WP + (min(lane + 32 * i, 79) * 10 + b) * 4);
#pragma unroll
          for (int i = 0; i < 3; i++) {
            const int k = lane + 32 * i, j = k / 20;
            if (k < 80) sts128(sb + SM_WPHI + b * 1280 + k * 16, j == 0 ? w[i] : 0u, j == 1 ? w[i] : 0u, j == 2 ? w[i] : 0u, j == 3 ? w[i] : 0u);
          }
        }
        STAMP_IF(ht == 0, 48);
        bar_arrive<3, 320>();
      }
      mbar_wait(sb + BAR_MAIN, 0);
      mbar_wait(sb + BAR_K0, 0);
      mbar_wait(sb + BAR_PRF, 0);
      if (ht < 48) sts128(sb + SM_UB0 + ht * 16, 0u, 0u, 0u, 0u);
#pragma unroll 1
      for (int i = ht; i < 192; i += 96) {
        const uint32_t a = i < 48 ? SM_PT0 + (i / 24) * 2432 + (i % 24) * 16 + ((i % 24) >= 8 ? 2048 : 0) : SM_H + (i >= 120 ? 1024 : 0) + (i - 48) * 16;
        sts128(sb + a, 0u, 0u, 0u, 0u);
      }
      if (ht >= 32) build_bands(sb + SM_W, ht - 32);
      bar_sync<12, 96>();
      {
#pragma unroll 1
        for (int i5 = 0; i5 < 5; i5++) {
          const int c = i5 < 3 ? i5 : 7 - i5;
          const uint32_t pt = sb + (c == 4 ? SM_PT4 : (c & 1) ? SM_PT1 : SM_PT0), hh = sb + (c == 4 ? SM_H4 : SM_H);
          const uint32_t ub = sb + (c == 4 ? SM_UB4 : (c & 1) ? SM_UB1 : SM_UB0);
          if (c > 0) mbar_wait(sb + (c == 4 ? BAR_AXF : BAR_FREE), c == 2);
          if (c > 1 && ht == 32) {
            const uint32_t bar = sb + (c == 4 ? BAR_RD4 : BAR_UB + 8 * (c & 1));
            if (c == 4) asm volatile("mbarrier.expect_tx.relaxed.cta.shared::cta.b64 [%0], 4096;" ::"r"(bar) : "memory");
            else mbar_expect(bar, 4096);
            bulk_load(ub + UB_Z * 32, g_uT + (cta * 5 + c) * 2048, 4096, bar);
          }
          __syncwarp();
          if (wp == 1) {
            if (c == 1 || c == 4) {
#pragma unroll 1
              for (int i = lane; i < 48; i += 32) sts128(ub + i * 16, 0u, 0u, 0u, 0u);
#pragma unroll 1
              for (int i = lane; i < 48; i += 32) sts128(pt + (i / 24) * 2432 + (i % 24) * 16 + ((i % 24) >= 8 ? 2048 : 0), 0u, 0u, 0u, 0u);
              __syncwarp();
            }
            build_taps<2>(sb + SM_KZ + c * 1296, pt, lane, 32);
          } else {
            if (c == 4) {
#pragma unroll 1
              for (int i = lane; i < 72; i += 32) sts128(hh + (wp - 2) * 2176 + i * 16, 0u, 0u, 0u, 0u);
            }
            build_taps<1>(sb + SM_KZ + c * 1296, pt, ht + 32, 0);
            build_far_taps<2>(sb + SM_KZ + c * 1296, hh, ht - 32, 64);
          }
          fence_async_smem();
          mbar_arrive(sb + (c == 4 ? BAR_RD4 : c == 3 ? BAR_RD3 : BAR_RDY));
          if (c == 0 && ht == 32) {
            mbar_wait(sb + BAR_KGD, 0);
            mbar_expect(sb + BAR_UB + 8, 4096);
            bulk_load(sb + SM_UB1 + UB_Z * 32, g_uT + (cta * 5 + 1) * 2048, 4096, sb + BAR_UB + 8);
          }
          __syncwarp();
          STAMP_IF(lane == 0 && c == 1 && wp < 3, 49 + wp);
        }
      }
    }
  } else if (tid >= 256) {
    asm volatile("setmaxnreg.dec.sync.aligned.u32 120;");
    LANE_IDS
    const int bt = tid_ - 256;
    const int grp = cta >> 5, gi = cta & 31;
    const int ch0 = cta * 5;
    {
      uint32_t pa[3], pc[3], pex = 0;
      const uint32_t dtl = __bfloat16_as_ushort(__float2bfloat16_rn(expf(bf2f(rawc))));
      auto prep = [&](auto nc, int c0) {
        constexpr int N = nc;
        Cx cc[N];
#pragma unroll
        for (int c = 0; c < N; c++) {
          const float dt = bf2f(__shfl_sync(0xffffffffu, dtl, c0 + c));
          pa[c] = raw[c][0] | (raw[c][1] << 16);
          cc[c] = cmul(Cx{bf2f(raw[c][4]), bf2f(raw[c][5])}, Cx{dt * bf2f(raw[c][2]), dt * bf2f(raw[c][3])});
          const unsigned m = __reduce_max_sync(0xffffffffu, __float_as_uint(fmaxf(fabsf(cc[c].re), fabsf(cc[c].im))));
          if (lane == 0) sts32(sb + SM_CMAX + (c0 + c) * 16 + wp * 4, m);
        }
        bar_sync<2, 128>();
#pragma unroll
        for (int c = 0; c < N; c++) {
          const uint4 m4 = lds128(sb + SM_CMAX + (c0 + c) * 16);
          const unsigned ex = min(max(max(max(m4.x, m4.y), max(m4.z, m4.w)) >> 23, 1u), 253u) << 23;
          const float scale = __uint_as_float((254u << 23) - ex);
          pc[c] = pack_f16(cc[c].re * scale, cc[c].im * scale);
          if (lane == c0 + c) pex = ex;
        }
      };
      pa[2] = pc[2] = 0u;
      prep(IC<2>{}, 0);
      auto taps = [&](float* kd, int c) {
        store_taps(kd, __uint_as_float(__shfl_sync(0xffffffffu, pex, c)), __uint_as_float(__shfl_sync(0xffffffffu, rawc, 5 + c) << 16), sb + SM_KZ + c * 1296, bt & 63);
      };
      auto anchors = [&](int c, Anchors& a) {
        const float dt = bf2f(__shfl_sync(0xffffffffu, dtl, c));
        const float2 cs = __half22float2(*reinterpret_cast<const __half2*>(&pc[0]));
        ssm_anchors(dt * bf2f(pa[0]) * 1.4426950408889634f, dt * __uint_as_float(pa[0] & 0xffff0000u), Cx{cs.x, cs.y}, a);
#pragma unroll
        for (int i = 0; i < 2; i++) { pa[i] = pa[i + 1]; pc[i] = pc[i + 1]; }
      };
#pragma unroll 1
      for (int c = 0; c < 2; c++) {
        Anchors a;
        anchors(c, a);
        if (c == 1) {
          float kd[12];
          wg_fence();
          ssm_gemm(kd, sb + SM_KG);
          wg_wait<0>();
          pin<12>(kd);
          if (wp < 2) taps(kd, 0);
          mbar_arrive(sb + BAR_K0);
          bar_sync<2, 128>();
        }
        pin<NANCH>(reinterpret_cast<uint32_t*>(&a));
        store_factors(a, sb + SM_KG, sb + SM_KG + 16384, bt);
        fence_async_smem();
        bar_sync<2, 128>();
        STAMP_IF(bt == 0, c == 1 ? 38 : 21);
      }
      mbar_wait(sb + BAR_PRM, 0);
#pragma unroll
      for (int k = 0; k < 3; k++)
#pragma unroll
        for (int i = 0; i < 6; i++) raw[k][i] = lds16(sb + SM_UB0 + i * 768 + k * 256 + bt * 2);
      prep(IC<3>{}, 2);
      fence_async_smem();
      mbar_arrive(sb + BAR_PRF);
      Anchors a, held, held2;
#pragma unroll
      for (int i = 0; i < NANCH; i++) reinterpret_cast<uint32_t*>(&a)[i] = reinterpret_cast<uint32_t*>(&held)[i] = 0u;
#pragma unroll 1
      for (int c = 2; c < 5; c++) {
        held2 = held;
        held = a;
        anchors(c, a);
        STAMP_IF(bt == 0 && c != 2, 21 + c);
      }
      mbar_wait(sb + STORE2_AT, 0);
      STAMP_IF(bt == 0, 37);
#pragma unroll 1
      for (int i = 0; i < 3; i++) {
        pin<NANCH>(reinterpret_cast<uint32_t*>(&held2));
        store_factors(held2, sb + SM_KG2 + (i >> 1) * 16384, sb + (i ? SM_KG + (i >> 1) * 12288 : SM_KG2 + 16384), bt);
        held2 = held;
        held = a;
        if (i != 1) {
          fence_async_smem();
          bar_sync<2, 128>();
        }
        if (i == 0) {
          mbar_wait(sb + BAR_MAIN, 0);
          float kd[24];
          wg_fence();
          ssm_gemm(kd, sb + SM_KG);
          ssm_gemm(kd + 12, sb + SM_KG2);
          wg_wait<0>();
          pin<24>(kd);
          if (wp < 2) { taps(kd, 1); taps(kd + 12, 2); }
          bar_sync<2, 128>();
          STAMP_IF(bt == 0, 23);
        }
      }
      STAMP_IF(bt == 0, 39);
      float k2[24];
      wg_fence();
      ssm_gemm2(k2, sb + SM_KG2, sb + SM_KG);
      wg_wait<0>();
      pin<24>(k2);
      mbar_arrive(sb + BAR_KGD);
#pragma unroll
      for (int i = 0; i < 12; i++) k2[i] = wp < 2 ? k2[i] : k2[12 + i];
      taps(k2, 3 + (wp >> 1));
    }
    STAMP_IF(bt == 0, 22);
    mbar_wait(sb + BAR_EPOCH, 0);
    const unsigned epoch = lds32(sb + SM_EPOCH);
#pragma unroll 1
    for (int c = 0; c < 3; c++) {
      mbar_wait(sb + BAR_RDY, c & 1);
      STAMP_IF(bt == 0 && c == 0, 33);
      mbar_wait(sb + BAR_UB + 8 * (c & 1), (c >> 1) & 1);
      STAMP_IF(bt == 0 && c == 1, 34);
      float y[64];
      conv_mma(y, sb + SM_W, sb + ((c & 1) ? SM_UB1 : SM_UB0), sb + ((c & 1) ? SM_PT1 : SM_PT0), sb + SM_H, sb + BAR_FREE, wp, lane);
      if (c == 2 && lane == 0) mbar_arrive(sb + BAR_CV);
      STAMP_IF(bt == 0 && c == 1, 35);
      if (c > 0) mbar_wait(sb + BAR_XF, (c - 1) & 1);
      conv_store(2, y, sb + SM_XCH, sb + SM_XCH2, g_yT + (ch0 + c) * 1024, wp, lane);
      if (lane == 0) mbar_arrive(sb + BAR_XF);
      STAMP_IF(bt == 0, 26 + c);
    }
    bar_sync<15, 384>();
    if (bt == 0) {
      signal(CNT_Y + grp);
      wait_count(CNT_Y + grp, (epoch + 1) * 32);
    }
    bar_sync<2, 128>();
    STAMP_IF(bt == 0, 31);
    {
      uint4 L[3][4];
#pragma unroll
      for (int bi = 0; bi < 3; bi++) {
        const int blk = wp + 4 * bi;
        if (blk < 10) {
          const int m = 2 * gi + blk / 5, c0 = 160 * grp + 32 * (blk % 5);
#pragma unroll
          for (int j = 0; j < 4; j++)
            L[bi][j] = __ldcg(reinterpret_cast<const uint4*>(g_yT + (c0 + 8 * (g >> 1) + 2 * j + (g & 1)) * 1024 + m * 16 + 4 * q));
        }
      }
#pragma unroll
      for (int bi = 0; bi < 3; bi++) {
        const int blk = wp + 4 * bi;
        if (blk < 10) {
          const int m = 2 * gi + blk / 5, c0 = 160 * grp + 32 * (blk % 5);
          transpose_store(L[bi], reinterpret_cast<uint4*>(P.outp + (size_t)(32 * m + 16 * (g & 1) + 4 * (g >> 1)) * 1280 + 640 + c0 + 8 * q), 160);
        }
      }
    }
    STAMP_IF(bt == 0, 32);
  } else {
    asm volatile("setmaxnreg.inc.sync.aligned.u32 168;");
    const int wg = tid >> 7;
    uint32_t qf[20], kf[20];
    float pk[40], pq[40];
    {
      float acc[120];
#pragma unroll
      for (int i = 0; i < 120; i++) acc[i] = 0.f;
      auto qkv_wait = [&](int it) { mbar_wait(sb + BAR_FULL + 8 * (it & 3), (it >> 2) & 1); };
      auto qkv_step = [&](int it) {
        const uint32_t d = sb + (it & 3) * STAGE;
        const uint32_t da = dlo(d + wg * 8192, 16), db1 = dlo(d + OFF_W128, 8192), db2 = dlo(d + OFF_W16, 2048);
        static_for<0, 4>([&](auto k) {
          mma_qkv192<k * 2, dhi(1024, 1), k * 128, dhi(1024, 1)>(acc, da, db1);
          mma_qkv48<k * 2, dhi(1024, 1), k * 32, dhi(256, 3)>(acc + 96, da, db2);
        });
        wg_commit();
      };
      auto release = [&](int it) {
        if (it < 8 && (tid & 127) == 0) mbar_arrive(it < 6 ? sb + BAR_EMPTY + 8 * (it & 3) : sb + BAR_S6 + 8 * (it - 6));
      };
#pragma unroll 1
      for (int it = 0; it < 10; it++) {
        qkv_wait(it);
        STAMP_IF(tid == 0 && it == 0, 0);
        wg_fence();
        qkv_step(it);
        if (it > 0) {
          wg_wait<1>();
          release(it - 1);
        }
      }
      wg_wait<0>();
      pin<120>(acc);
      if ((tid & 127) == 0) mbar_arrive(sb + BAR_MAIN);
      STAMP_IF(tid == 0, 1);
#pragma unroll
      for (int i = 0; i < 16; i++) {
        qf[i] = pack_bf16(acc[2 * i], acc[2 * i + 1]);
        kf[i] = pack_bf16(acc[32 + 2 * i], acc[33 + 2 * i]);
      }
#pragma unroll
      for (int i = 0; i < 4; i++) {
        qf[16 + i] = pack_bf16(acc[96 + 2 * i], acc[97 + 2 * i]);
        kf[16 + i] = pack_bf16(acc[104 + 2 * i], acc[105 + 2 * i]);
      }
      bar_sync<3, 320>();
      fence_async_smem();
      ROW_IDS
      const uint32_t va = sb + SM_V + row * 16 + q * 4;
#pragma unroll
      for (int b = 0; b < 10; b++) {
        const float* a = b < 8 ? acc + 64 + 4 * b : acc + 112 + 4 * (b - 8);
        sts32(va + (b + (b >= 5)) * 2048, pack_bf16(a[0], a[1]));
        sts32(va + (b + (b >= 5)) * 2048 + 128, pack_bf16(a[2], a[3]));
      }
      sts128(sb + SM_V + 10240 + wg * 12288 + (tid_ & 127) * 16, 0x3F803F80u, 0x3F803F80u, 0x3F803F80u, 0x3F803F80u);
      wg_fence();
      mma_phi80_z<0, dhi(1280, 0)>(pk, kf[0], kf[1], kf[2], kf[3], dlo(sb + SM_WPHI, 128));
      static_for<1, 5>([&](auto c) { mma_phi80<c * 16, dhi(1280, 0)>(pk, kf[4 * c], kf[4 * c + 1], kf[4 * c + 2], kf[4 * c + 3], dlo(sb + SM_WPHI, 128)); });
      wg_commit();
      mma_phi80_z<0, dhi(1280, 0)>(pq, qf[0], qf[1], qf[2], qf[3], dlo(sb + SM_WPHI, 128));
      static_for<1, 5>([&](auto c) { mma_phi80<c * 16, dhi(1280, 0)>(pq, qf[4 * c], qf[4 * c + 1], qf[4 * c + 2], qf[4 * c + 3], dlo(sb + SM_WPHI, 128)); });
      wg_commit();
    }
    wg_wait<1>();
    pin<40>(pk);
    pin<20>(kf);
    STAMP_IF(tid == 0, 2);
    {
      uint32_t ph[20];
      ROW_IDS
      const uint32_t ad = sb + SM_PHIK + q * 5 * PHIK_S + row * 16;
      dual_softmax<0>(pk, ph);
#pragma unroll
      for (int i = 0; i < 5; i++) sts128(ad + i * PHIK_S, ph[4 * i], ph[4 * i + 1], ph[4 * i + 2], ph[4 * i + 3]);
      dual_softmax<1>(pk, ph);
#pragma unroll
      for (int i = 0; i < 5; i++) sts128(ad + i * PHIK_S + 128, ph[4 * i], ph[4 * i + 1], ph[4 * i + 2], ph[4 * i + 3]);
    }
    wg_wait<0>();
    pin<40>(pq);
    if ((tid & 127) == 0) mbar_arrive(sb + BAR_PHI);
    fence_async_smem();
    STAMP_IF(tid == 0, 3);
    bar_sync<1, 256>();
    const unsigned epoch = lds32(sb + SM_EPOCH);
    {
      float kv[40];
      const uint32_t da = dlo(sb + SM_V + wg * 12288, 128), db = dlo(sb + SM_PHIK + wg * 10 * PHIK_S, 128);
      wg_fence();
      mma_kv80_z<0, dhi(2048, 0), 0, dhi(PHIK_S, 0)>(kv, da, db);
      static_for<1, 8>([&](auto k) { mma_kv80<k * 16, dhi(2048, 0), k * 16, dhi(PHIK_S, 0)>(kv, da, db); });
      wg_commit();
      wg_wait<0>();
      pin<40>(kv);
      bar_sync<1, 256>();
      LANE_IDS
      if (wp < 3) {
#pragma unroll
        for (int h = 0; h < 2; h++) {
          const int dr = 16 * wp + 8 * h + g;
          if (dr < 40) {
            const int hi = dr >= 20, dd = dr - 20 * hi;
            const uint32_t p = sb + SM_KVST + q * 720 + (8 * (dd >> 1) + 2 * (2 * wg + hi) + (dd & 1)) * 8;
#pragma unroll
            for (int i = 0; i < 5; i++)
              sts64(p + i * 2880, __float_as_uint(hi ? kv[20 + 4 * i + 2 * h] : kv[4 * i + 2 * h]), __float_as_uint(hi ? kv[21 + 4 * i + 2 * h] : kv[4 * i + 2 * h + 1]));
          } else if (g < 2) {
            const uint32_t p = sb + SM_KVST + q * 720 + (80 + 2 * (2 * wg + g)) * 8;
#pragma unroll
            for (int i = 0; i < 5; i++)
              sts64(p + i * 2880, __float_as_uint(g ? kv[22 + 4 * i] : kv[4 * i + 2]), __float_as_uint(g ? kv[23 + 4 * i] : kv[4 * i + 3]));
          }
        }
      }
      fence_async_smem();
      bar_arrive<4, 288>();
    }
    STAMP_IF(tid == 0, 4);
    uint32_t pa[20], pb[20];
    dual_softmax<0>(pq, pa);
    dual_softmax<1>(pq, pb);
    STAMP_IF(tid == 0, 5);
    {
      if (tid == 0) wait_count(CNT_KV + hg, (epoch + 1) * 16);
      bar_sync<1, 256>();
      STAMP_IF(tid == 0, 6);
      LANE_IDS
      const float2* src = reinterpret_cast<const float2*>(g_kv + (epoch & 1) * 28800 + hg * 3600) + tid_;
      float2 t[8];
#pragma unroll
      for (int i = 0; i < 8; i++)
        if (i < 7 || tid_ < 8) t[i] = __ldcg(src + 256 * i);
      int n = tid_ % 90;
#pragma unroll
      for (int i = 0; i < 8; i++) {
        if (i < 7 || tid_ < 8) {
          const int j = (n >> 1) & 3;
          const uint32_t w = pack_bf16(t[i].x, t[i].y);
          sts128(sb + SM_KVB + (tid_ + 256 * i) * 16, j == 0 ? w : 0u, j == 1 ? w : 0u, j == 2 ? w : 0u, j == 3 ? w : 0u);
        }
        n = n < 14 ? n + 76 : n - 14;
      }
      if (tid_ == 255) mbar_arrive(sb + BAR_KVB);
    }
    fence_async_smem();
    bar_sync<1, 256>();
    STAMP_IF(tid == 0, 7);
    {
      float o[44];
      wg_fence();
      mma_o88_z<0, dhi(128, 0)>(o, pa[0], pb[0], pa[1], pb[1], dlo(sb + SM_KVB, 1440));
      static_for<1, 10>([&](auto c) { mma_o88<c * 180, dhi(128, 0)>(o, pa[2 * c], pb[2 * c], pa[2 * c + 1], pb[2 * c + 1], dlo(sb + SM_KVB, 1440)); });
      wg_commit();
      wg_wait<0>();
      pin<44>(o);
      pin<20>(pa);
      pin<20>(pb);
      STAMP_IF(tid == 0, 8);
      ROW_IDS
      const float r0 = 1.0f / (o[40] + 1e-6f), r1 = 1.0f / (o[42] + 1e-6f);
      const uint32_t d0 = sb + SM_OST + row * 160 + q * 40;
#pragma unroll
      for (int i = 0; i < 5; i++) {
        sts64(d0 + 8 * i, pack_bf16(o[8 * i] * r0, o[8 * i + 1] * r0), pack_bf16(o[8 * i + 4] * r0, o[8 * i + 5] * r0));
        sts64(d0 + 8 * i + 1280, pack_bf16(o[8 * i + 2] * r1, o[8 * i + 3] * r1), pack_bf16(o[8 * i + 6] * r1, o[8 * i + 7] * r1));
      }
      fence_async_smem();
      bar_arrive<5, 288>();
    }
    STAMP_IF(tid == 0, 9);
    {
      LANE_IDS
      if (wg == 0) {
        mbar_wait(sb + BAR_RD4, 0);
      } else {
        mbar_wait(sb + BAR_RD3, 0);
        mbar_wait(sb + BAR_UB + 8, 1);
      }
      const uint32_t x = sb + (wg ? SM_PT1 : SM_UB4);
      float y[64];
      conv_mma(y, sb + SM_W, sb + (wg ? SM_UB1 : SM_UB4), sb + (wg ? SM_PT1 : SM_PT4), sb + (wg ? SM_H : SM_H4), 0, wp, lane);
      if (lane == 0) mbar_arrive(sb + BAR_CV);
      asm volatile("bar.sync %0, 128;" ::"r"(7 + wg) : "memory");
      conv_store(7 + wg, y, x, x + 4096, g_yT + (cta * 5 + 4 - wg) * 1024, wp, lane);
      fence_async_smem();
      __syncwarp();
      if (wg == 0 && lane == 0) mbar_arrive(sb + BAR_CVA);
      bar_arrive<15, 384>();
      STAMP_IF((tid & 127) == 0, 13 + wg);
    }
    float acc[40];
#pragma unroll
    for (int i = 0; i < 40; i++) acc[i] = 0.f;
    mbar_wait(sb + BAR_WO, 0);
    mbar_wait(sb + BAR_CV, 0);
#pragma unroll 1
    for (int it = 0; it < 10; it++) {
      const int s = it < 5 ? it : it - 5;
      mbar_wait(sb + BAR_OFULL + 8 * s, it >= 5);
      STAMP_IF(tid == 0 && it == 0, 10);
      const uint32_t da = dlo(sb + (s < 4 ? s * 16384 : SM_O4) + wg * 8192, 16), db = dlo(sb + SM_WO + it * 10240, 2048);
      wg_fence();
      static_for<0, 4>([&](auto k) { mma_out80<k * 2, dhi(1024, 1), k * 32, dhi(256, 3)>(acc, da, db); });
      wg_commit();
      if (it > 0) {
        wg_wait<1>();
        if (it < 6 && (tid & 127) == 0) mbar_arrive(sb + BAR_OEMPTY + 8 * (it - 1));
      }
    }
    wg_wait<0>();
    pin<40>(acc);
    STAMP_IF(tid == 0, 11);
    bar_sync<1, 256>();
    {
      LANE_IDS
      const uint32_t st = sb + wg * 10240;
      const uint32_t ad = st + (wp * 16 + (lane & 15)) * 160 + (lane >> 4) * 16;
#pragma unroll
      for (int i = 0; i < 5; i++) {
        asm volatile("stmatrix.sync.aligned.m8n8.x4.shared.b16 [%0], {%1,%2,%3,%4};" ::"r"(ad + i * 32),
                     "r"(pack_bf16(acc[8 * i], acc[8 * i + 1])), "r"(pack_bf16(acc[8 * i + 2], acc[8 * i + 3])),
                     "r"(pack_bf16(acc[8 * i + 4], acc[8 * i + 5])), "r"(pack_bf16(acc[8 * i + 6], acc[8 * i + 7])) : "memory");
      }
      fence_async_smem();
      STAMP_IF(tid == 0, 16);
      if (wg == 0) bar_sync<7, 128>(); else bar_sync<8, 128>();
      STAMP_IF(tid == 0, 17);
      if ((tid & 127) == 0) {
        tma2d_store(&P.out, st, hg * 80, rb * 128 + wg * 64);
        asm volatile("cp.async.bulk.commit_group;" ::: "memory");
        asm volatile("cp.async.bulk.wait_group.read 0;" ::: "memory");
      }
    }
    STAMP_IF(tid == 0, 12);
  }
}

typedef CUresult (*EncodeFn)(CUtensorMap*, CUtensorMapDataType, cuuint32_t, void*, const cuuint64_t*, const cuuint64_t*,
                             const cuuint32_t*, const cuuint32_t*, CUtensorMapInterleave, CUtensorMapSwizzle,
                             CUtensorMapL2promotion, CUtensorMapFloatOOBfill);

void encode(EncodeFn fn, CUtensorMap* m, const void* p, int rank, const cuuint64_t* dims, const cuuint64_t* strides,
            const cuuint32_t* box, CUtensorMapSwizzle sw) {
  const cuuint32_t es[5] = {1, 1, 1, 1, 1};
  fn(m, CU_TENSOR_MAP_DATA_TYPE_BFLOAT16, rank, const_cast<void*>(p), dims, strides, box, es, CU_TENSOR_MAP_INTERLEAVE_NONE, sw,
     CU_TENSOR_MAP_L2_PROMOTION_NONE, CU_TENSOR_MAP_FLOAT_OOB_FILL_NONE);
}

int build_tile_map(uint8_t* map) {
  int dev = 0, nsm = 0;
  cudaGetDevice(&dev);
  cudaDeviceGetAttribute(&nsm, cudaDevAttrMultiProcessorCount, dev);
  if (nsm > 192) nsm = 192;
  for (int i = 0; i < 192; i++) map[i] = (uint8_t)(i < NCTA ? i : 255);
  cudaFuncSetAttribute(fused_kernel, cudaFuncAttributeNonPortableClusterSizeAllowed, 1);
  int f[17] = {0};
  for (int c = 2; c <= 16; c++) {
    cudaLaunchConfig_t cfg = {};
    cfg.gridDim = dim3(c);
    cfg.blockDim = dim3(512);
    cfg.dynamicSmemBytes = SMEM_BYTES;
    cudaLaunchAttribute at[1];
    at[0].id = cudaLaunchAttributeClusterDimension;
    at[0].val.clusterDim.x = c; at[0].val.clusterDim.y = 1; at[0].val.clusterDim.z = 1;
    cfg.attrs = at;
    cfg.numAttrs = 1;
    if (cudaOccupancyMaxActiveClusters(&f[c], fused_kernel, &cfg) != cudaSuccess) { cudaGetLastError(); return nsm; }
  }
  int n[10];
  n[5] = f[10]; n[6] = f[12]; n[7] = f[14]; n[8] = f[16];
  n[9] = f[9] - n[5];
  n[4] = f[8] - n[8];
  n[3] = f[6] - n[6] - n[9];
  n[2] = f[4] - n[4] - n[6] - n[8];
  n[1] = n[2];
  int ntpc = 0;
  for (int r = 1; r <= 9; r++) ntpc += n[r];
  if (2 * f[2] != nsm || ntpc > f[2] || n[1] > 8 || n[9] < 0 || nsm < NCTA) return nsm;
  for (int r = 1; r < 9; r++) if (n[r] < n[r + 1]) return nsm;
  int pair_of[96];
  bool taken[64] = {false};
  int t = 0;
  for (int r = 1; r <= 9; r++)
    for (int p = n[1] - n[r]; p < n[1]; p++, t++) {
      pair_of[t] = r <= 8 ? p * 8 + r - 1 : -1;
      if (r <= 8) taken[pair_of[t]] = true;
    }
  for (; t < f[2]; t++) pair_of[t] = -1;
  for (int pr = 0; pr < 64; pr++)
    for (int u = f[2] - 1; u >= 0 && !taken[pr]; u--)
      if (pair_of[u] < 0) { pair_of[u] = pr; taken[pr] = true; }
  for (int u = 0; u < f[2]; u++)
    for (int e = 0; e < 2; e++) {
      const int pr = pair_of[u], blk = pr >> 3, i = pr & 7;
      map[2 * u + e] = pr < 0 ? 255 : (uint8_t)(((blk >> 1) * 4 + (i & 1) * 2 + e) * 8 + (blk & 1) * 4 + (i >> 1));
    }
  return nsm;
}

}

extern "C" void kernel_launch(void* const* d_in, const int* in_sizes, int n_in, void* d_out, int out_size) {
  (void)in_sizes; (void)n_in; (void)out_size;
  void* fnp = nullptr;
  cudaDriverEntryPointQueryResult qr;
  cudaGetDriverEntryPoint("cuTensorMapEncodeTiled", &fnp, cudaEnableDefault, &qr);
  EncodeFn fn = (EncodeFn)fnp;
  void* O = nullptr;
  cudaGetSymbolAddress(&O, g_O);

  Params P;
  { const cuuint64_t d[2] = {640, 2048}, s[1] = {1280}; const cuuint32_t b[2] = {64, 128};
    encode(fn, &P.x, d_in[0], 2, d, s, b, CU_TENSOR_MAP_SWIZZLE_128B);
    encode(fn, &P.o, O, 2, d, s, b, CU_TENSOR_MAP_SWIZZLE_128B);
    const cuuint32_t b2[2] = {80, 128};
    encode(fn, &P.ost, O, 2, d, s, b2, CU_TENSOR_MAP_SWIZZLE_NONE); }
  { const cuuint64_t d[3] = {640, 640, 3}, s[2] = {3840, 1280}; const cuuint32_t b1[3] = {64, 64, 3}, b2[3] = {16, 64, 3};
    encode(fn, &P.w128, d_in[1], 3, d, s, b1, CU_TENSOR_MAP_SWIZZLE_128B);
    encode(fn, &P.w16, d_in[1], 3, d, s, b2, CU_TENSOR_MAP_SWIZZLE_32B); }
  { const cuuint64_t d[3] = {16, 640, 40}, s[2] = {1280, 32}; const cuuint32_t b[3] = {16, 64, 5};
    encode(fn, &P.wo, d_in[3], 3, d, s, b, CU_TENSOR_MAP_SWIZZLE_32B); }
  { const cuuint64_t d[2] = {1280, 2048}, s[1] = {2560}; const cuuint32_t b[2] = {80, 64};
    encode(fn, &P.out, d_out, 2, d, s, b, CU_TENSOR_MAP_SWIZZLE_NONE); }
  P.wphi = (const uint32_t*)d_in[2];
  P.u = (const __nv_bfloat16*)d_in[4];
  for (int i = 0; i < 6; i++) P.ssm[i] = (const uint16_t*)d_in[5 + i];
  P.logdt = (const uint16_t*)d_in[11]; P.dskip = (const uint16_t*)d_in[12];
  P.outp = (__nv_bfloat16*)d_out;

  cudaFuncSetAttribute(fused_kernel, cudaFuncAttributeMaxDynamicSharedMemorySize, SMEM_BYTES);
  static int nsm = 0;
  static uint8_t tile_map[192];
  if (nsm == 0) nsm = build_tile_map(tile_map);
  for (int i = 0; i < 192; i++) P.tile_of_sm[i] = tile_map[i];
  P.nsm = nsm;
  for (int i = 0; i < 36; i++) P.bar_count[i] = (uint8_t)(((BAR_COUNT2 >> (i & 31)) & 1) + 1);
  P.bar_count[(BAR_PHI - SM_MISC) / 8] = 2;
  P.bar_count[(BAR_K0 - SM_MISC) / 8] = P.bar_count[(BAR_PRF - SM_MISC) / 8] = P.bar_count[(BAR_KGD - SM_MISC) / 8] = 128;
  P.bar_count[(BAR_RDY - SM_MISC) / 8] = 96;
  P.bar_count[(BAR_XF - SM_MISC) / 8] = P.bar_count[(BAR_FREE - SM_MISC) / 8] = 4;

  fused_kernel<<<nsm, 512, SMEM_BYTES, cudaStreamPerThread>>>(P);
}
```
